```python
import torch

def _softmax(x, axis=-1):
    return torch.softmax(x, dim=axis)
def _gelu(x):
    return torch.nn.functional.gelu(x, approximate="tanh")
def _silu(x):
    return torch.nn.functional.silu(x)
def _sigmoid(x):
    return torch.sigmoid(x)
def _layernorm(x, axis=-1, eps=1e-5):
    m = x.mean(dim=axis, keepdim=True)
    v = x.var(dim=axis, keepdim=True, unbiased=False)
    return (x - m) / torch.sqrt(v + eps)
def _scatter_add(tgt, idx, src, axis=0):
    return tgt.clone().index_add_(axis, idx, src)
def _segment_sum(src, seg, n):
    out = torch.zeros((n,) + src.shape[1:], dtype=src.dtype)
    return out.index_add_(0, seg, src)
def _pad(x, pw):
    flat = tuple(v for pair in reversed(pw) for v in pair)
    return torch.nn.functional.pad(x, flat)

kernel_name = 'standalone__edge_featured_mpnn_egc__graph'

def setup_inputs():

    _w = (lambda a: (lambda t: t.to(torch.bfloat16) if t.is_floating_point() else t)(torch.as_tensor(a)))
    N, deg, D, De = 10000, 16, 128, max(16, 1)
    E = N * deg
    return {
        "x": _w((lambda *s: torch.randn(*s, dtype=torch.bfloat16) * 0.1)(N, D)),
        "e_attr": _w((lambda *s: torch.randn(*s, dtype=torch.bfloat16) * 0.1)(E, De)),
        "src": _w((lambda lo, hi, *s: torch.randint(lo, hi, s))(0, N, E).to(torch.int64)),
        "dst": _w((lambda lo, hi, *s: torch.randint(lo, hi, s))(0, N, E).to(torch.int64)),
        "u_w": _w((lambda *s: torch.randn(*s, dtype=torch.bfloat16) * 0.05)(D, D)),
        "v_w": _w((lambda *s: torch.randn(*s, dtype=torch.bfloat16) * 0.05)(D, D)),
        "g_w": _w((lambda *s: torch.randn(*s, dtype=torch.bfloat16) * 0.1)(2 * D + De, D)),
    }

def reference(x, e_attr, src, dst, u_w, v_w, g_w):
    N, D = x.shape
    g_in = torch.concatenate([x[dst], x[src], e_attr], axis=-1)
    eta = _sigmoid(g_in @ g_w)
    hv = x @ v_w
    msg = eta * hv[src]
    agg = _segment_sum(msg, dst, N)
    return _silu(x @ u_w + agg)
```

```cpp
#include <cuda_runtime.h>
#include <cuda.h>
#include <cuda_bf16.h>
#include <stdint.h>

#define EGC_PF_BAR 1
namespace egc {

constexpr int kN = 10000;
constexpr int kE = 160000;
constexpr int kG = 132;
constexpr int kEPB = 1216;
constexpr int kWarps = 12;
constexpr int kThreads = kWarps * 32;
constexpr int kSlot = 32;
constexpr int kRows = 88;
constexpr int kLCap = 1536;
constexpr uint32_t kTab = kN * 256;
constexpr uint32_t kSentinel = 0xFFFFFFFFu;
constexpr uint32_t kOverflow = 126u << 25;
constexpr uint32_t kPadRec = 127u << 25;
constexpr int kSpinLimit = 1 << 22;
constexpr int kRingSlot = 4352;

static_assert(kN % 8 == 0 && kN < 16382, "src must fit 14 bits");
static_assert(kEPB * kG >= kE && kEPB <= 2048 && kEPB % 4 == 0 && kE % 4 == 0, "edge chunks");
static_assert(kG % kWarps == 0, "slot lines per warp");

constexpr int SM_X = 0;
constexpr int SM_W0 = 22528;
constexpr int SM_SLOT = SM_W0 + 4 * 16384;
constexpr int SM_RING = 0;
constexpr int SM_W4 = 105472;
constexpr int SM_LIST = SM_W4 + 4 * 16384;
constexpr int SM_OUT = SM_LIST + kLCap * 8;
constexpr int SM_WC = SM_OUT + kWarps * 2048;
constexpr int SM_NCNT = SM_WC + 16 * 256;
constexpr int SM_P = SM_NCNT + 640;
constexpr int SM_SCNT = SM_P + 384;
constexpr int SM_MBAR = SM_SCNT + 544;
constexpr int SM_PROF = SM_MBAR + 48;
constexpr int SM_TOTAL = SM_PROF + 80;
static_assert(SM_SLOT + kG * 128 <= SM_W4 && kWarps * 2 * kRingSlot <= SM_W4, "smem map");
static_assert(SM_W0 % 1024 == 0 && SM_W4 % 1024 == 0 && SM_WC % 1024 == 0 && SM_TOTAL <= 232448, "smem map");

__device__ __align__(1024) unsigned char g_T[2 * kTab];
__device__ __align__(1024) uint32_t g_slots[kG * kG * kSlot];
__device__ unsigned g_bar[64];
#define PROF(i)
#define PROFB(i)

__device__ __forceinline__ uint32_t smem_u32(const void* p) { return (uint32_t)__cvta_generic_to_shared(p); }
__device__ __forceinline__ void cp16(uint32_t dst, const void* src) {
    asm volatile("cp.async.cg.shared.global [%0], [%1], 16;" ::"r"(dst), "l"(src) : "memory");
}
__device__ __forceinline__ void cp16z(uint32_t dst, const void* src, uint32_t nbytes) {
    asm volatile("cp.async.cg.shared.global [%0], [%1], 16, %2;" ::"r"(dst), "l"(src), "r"(nbytes) : "memory");
}
__device__ __forceinline__ void cp8z(uint32_t dst, const void* src, uint32_t nbytes) {
    asm volatile("cp.async.ca.shared.global [%0], [%1], 8, %2;" ::"r"(dst), "l"(src), "r"(nbytes) : "memory");
}
__device__ __forceinline__ void named_arrive(int id, int n) { asm volatile("bar.arrive %0, %1;" ::"r"(id), "r"(n) : "memory"); }
__device__ __forceinline__ void named_wait(int id, int n) { asm volatile("bar.sync %0, %1;" ::"r"(id), "r"(n) : "memory"); }
__device__ __forceinline__ void grid_arrive(unsigned* ctr) {
    asm volatile("red.relaxed.gpu.global.add.u32 [%0], 1;" ::"l"(ctr) : "memory");
}
__device__ __forceinline__ void grid_wait(const unsigned* ctr, unsigned target) {
    unsigned v = 0;
    for (int it = 0; it < kSpinLimit; ++it) {
        asm volatile("ld.relaxed.gpu.global.u32 %0, [%1];" : "=r"(v) : "l"(ctr) : "memory");
        if ((int)(v - target) >= 0) break;
    }
}
__device__ __forceinline__ void cp_commit() { asm volatile("cp.async.commit_group;" ::: "memory"); }
template <int NPEND> __device__ __forceinline__ void cp_wait() { asm volatile("cp.async.wait_group %0;" ::"n"(NPEND) : "memory"); }
__device__ __forceinline__ void fence_async_smem() { asm volatile("fence.proxy.async.shared::cta;" ::: "memory"); }
template <int ID, int N> __device__ __forceinline__ void named_sync() { asm volatile("bar.sync %0, %1;" ::"n"(ID), "n"(N) : "memory"); }
__device__ __forceinline__ void bulk_store(void* gdst, uint32_t ssrc, uint32_t bytes) {
    asm volatile("cp.async.bulk.global.shared::cta.bulk_group [%0], [%1], %2;" ::"l"(gdst), "r"(ssrc), "r"(bytes) : "memory");
}
__device__ __forceinline__ void bulk_commit() { asm volatile("cp.async.bulk.commit_group;" ::: "memory"); }
__device__ __forceinline__ void mbar_init(uint32_t bar, uint32_t cnt) {
    asm volatile("mbarrier.init.shared::cta.b64 [%0], %1;" ::"r"(bar), "r"(cnt) : "memory");
}
__device__ __forceinline__ void mbar_expect(uint32_t bar, uint32_t bytes) {
    asm volatile("mbarrier.arrive.expect_tx.shared::cta.b64 _, [%0], %1;" ::"r"(bar), "r"(bytes) : "memory");
}
__device__ __forceinline__ void tma_load(uint32_t dst, const CUtensorMap* map, int col, int row, uint32_t bar) {
    asm volatile("cp.async.bulk.tensor.2d.shared::cluster.global.mbarrier::complete_tx::bytes [%0], [%1, {%3, %4}], [%2];"
                 ::"r"(dst), "l"(map), "r"(bar), "r"(col), "r"(row) : "memory");
}
__device__ __forceinline__ void mbar_arrive(uint32_t bar) {
    asm volatile("mbarrier.arrive.shared::cta.b64 _, [%0];" ::"r"(bar) : "memory");
}
__device__ __forceinline__ void mbar_wait(uint32_t bar, uint32_t parity) {
    uint32_t ok = 0;
    for (int it = 0; it < kSpinLimit && !ok; ++it) {
        asm volatile("{.reg .pred p; mbarrier.try_wait.parity.shared::cta.b64 p, [%1], %2; selp.u32 %0, 1, 0, p;}"
                     : "=r"(ok) : "r"(bar), "r"(parity) : "memory");
    }
}
__device__ __forceinline__ uint32_t lds32(uint32_t a) {
    uint32_t v;
    asm volatile("ld.shared.u32 %0, [%1];" : "=r"(v) : "r"(a) : "memory");
    return v;
}
__device__ __forceinline__ uint4 lds128(uint32_t a) {
    uint4 v;
    asm volatile("ld.shared.v4.u32 {%0,%1,%2,%3}, [%4];" : "=r"(v.x), "=r"(v.y), "=r"(v.z), "=r"(v.w) : "r"(a) : "memory");
    return v;
}
__device__ __forceinline__ void sts32(uint32_t a, uint32_t v) { asm volatile("st.shared.u32 [%0], %1;" ::"r"(a), "r"(v) : "memory"); }
__device__ __forceinline__ void sts64(uint32_t a, uint32_t x, uint32_t y) {
    asm volatile("st.shared.v2.u32 [%0], {%1,%2};" ::"r"(a), "r"(x), "r"(y) : "memory");
}
__device__ __forceinline__ void sts128(uint32_t a, uint32_t x, uint32_t y, uint32_t z, uint32_t w) {
    asm volatile("st.shared.v4.u32 [%0], {%1,%2,%3,%4};" ::"r"(a), "r"(x), "r"(y), "r"(z), "r"(w) : "memory");
}
__device__ __forceinline__ uint32_t atoms_inc(uint32_t a) {
    uint32_t old;
    asm volatile("atom.shared.add.u32 %0, [%1], 1;" : "=r"(old) : "r"(a) : "memory");
    return old;
}

__device__ __forceinline__ void ldsm4(uint32_t (&r)[4], uint32_t a) {
    asm volatile("ldmatrix.sync.aligned.m8n8.x4.shared.b16 {%0,%1,%2,%3}, [%4];"
                 : "=r"(r[0]), "=r"(r[1]), "=r"(r[2]), "=r"(r[3]) : "r"(a) : "memory");
}
__device__ __forceinline__ void ldsm4t(uint32_t (&r)[4], uint32_t a) {
    asm volatile("ldmatrix.sync.aligned.m8n8.x4.trans.shared.b16 {%0,%1,%2,%3}, [%4];"
                 : "=r"(r[0]), "=r"(r[1]), "=r"(r[2]), "=r"(r[3]) : "r"(a) : "memory");
}
__device__ __forceinline__ void stsm4t(uint32_t a, uint32_t r0, uint32_t r1, uint32_t r2, uint32_t r3) {
    asm volatile("stmatrix.sync.aligned.m8n8.x4.trans.shared.b16 [%0], {%1,%2,%3,%4};" ::"r"(a), "r"(r0), "r"(r1), "r"(r2), "r"(r3) : "memory");
}
__device__ __forceinline__ void stsm2t(uint32_t a, uint32_t r0, uint32_t r1) {
    asm volatile("stmatrix.sync.aligned.m8n8.x2.trans.shared.b16 [%0], {%1,%2};" ::"r"(a), "r"(r0), "r"(r1) : "memory");
}
__device__ __forceinline__ uint32_t pack_bf16(float lo, float hi) {
    uint32_t r;
    asm("cvt.rn.bf16x2.f32 %0, %1, %2;" : "=r"(r) : "f"(hi), "f"(lo));
    return r;
}
__device__ __forceinline__ uint32_t hfma2(uint32_t a, uint32_t b, uint32_t c) {
    uint32_t d;
    asm("fma.rn.bf16x2 %0, %1, %2, %3;" : "=r"(d) : "r"(a), "r"(b), "r"(c));
    return d;
}
__device__ __forceinline__ float tanh_fast(float x) {
    float r;
    asm("tanh.approx.f32 %0, %1;" : "=f"(r) : "f"(x));
    return r;
}
__device__ __forceinline__ void mma16z(float* d, uint32_t a0, uint32_t a1, uint32_t a2, uint32_t a3, uint32_t b0, uint32_t b1) {
    asm("mma.sync.aligned.m16n8k16.row.col.f32.bf16.bf16.f32 {%0,%1,%2,%3}, {%4,%5,%6,%7}, {%8,%9}, {%10,%10,%10,%10};"
        : "=f"(d[0]), "=f"(d[1]), "=f"(d[2]), "=f"(d[3])
        : "r"(a0), "r"(a1), "r"(a2), "r"(a3), "r"(b0), "r"(b1), "f"(0.f));
}
__device__ __forceinline__ void mma16(float* d, uint32_t a0, uint32_t a1, uint32_t a2, uint32_t a3, uint32_t b0, uint32_t b1) {
    asm("mma.sync.aligned.m16n8k16.row.col.f32.bf16.bf16.f32 {%0,%1,%2,%3}, {%4,%5,%6,%7}, {%8,%9}, {%0,%1,%2,%3};"
        : "+f"(d[0]), "+f"(d[1]), "+f"(d[2]), "+f"(d[3])
        : "r"(a0), "r"(a1), "r"(a2), "r"(a3), "r"(b0), "r"(b1));
}
__device__ __forceinline__ void mma8(float* d, uint32_t a0, uint32_t a1, uint32_t b0) {
    asm("mma.sync.aligned.m16n8k8.row.col.f32.bf16.bf16.f32 {%0,%1,%2,%3}, {%4,%5}, {%6}, {%0,%1,%2,%3};"
        : "+f"(d[0]), "+f"(d[1]), "+f"(d[2]), "+f"(d[3])
        : "r"(a0), "r"(a1), "r"(b0));
}
__device__ __forceinline__ uint32_t movm_t(uint32_t a) {
    uint32_t d;
    asm("movmatrix.sync.aligned.m8n8.trans.b16 %0, %1;" : "=r"(d) : "r"(a));
    return d;
}

__device__ __forceinline__ uint64_t make_desc(uint32_t lo) {
    uint64_t d;
    asm("mov.b64 %0, {%1, %2};" : "=l"(d) : "r"(lo), "r"(0x40000040u));
    return d;
}
__device__ __forceinline__ void wgmma_m64n88k16(float (&d)[44], uint64_t da, uint64_t db, int scale_d) {
    asm volatile(
        "{.reg .pred p; setp.ne.b32 p, %46, 0;\n"
        "wgmma.mma_async.sync.aligned.m64n88k16.f32.bf16.bf16 "
        "{%0,%1,%2,%3,%4,%5,%6,%7,%8,%9,%10,%11,%12,%13,%14,%15,%16,%17,%18,%19,%20,%21,"
        "%22,%23,%24,%25,%26,%27,%28,%29,%30,%31,%32,%33,%34,%35,%36,%37,%38,%39,%40,%41,%42,%43},"
        " %44, %45, p, 1, 1, 1, 0;}\n"
        : "+f"(d[0]), "+f"(d[1]), "+f"(d[2]), "+f"(d[3]), "+f"(d[4]), "+f"(d[5]), "+f"(d[6]), "+f"(d[7]),
          "+f"(d[8]), "+f"(d[9]), "+f"(d[10]), "+f"(d[11]), "+f"(d[12]), "+f"(d[13]), "+f"(d[14]), "+f"(d[15]),
          "+f"(d[16]), "+f"(d[17]), "+f"(d[18]), "+f"(d[19]), "+f"(d[20]), "+f"(d[21]), "+f"(d[22]), "+f"(d[23]),
          "+f"(d[24]), "+f"(d[25]), "+f"(d[26]), "+f"(d[27]), "+f"(d[28]), "+f"(d[29]), "+f"(d[30]), "+f"(d[31]),
          "+f"(d[32]), "+f"(d[33]), "+f"(d[34]), "+f"(d[35]), "+f"(d[36]), "+f"(d[37]), "+f"(d[38]), "+f"(d[39]),
          "+f"(d[40]), "+f"(d[41]), "+f"(d[42]), "+f"(d[43])
        : "l"(da), "l"(db), "r"(scale_d));
}

__device__ __forceinline__ int node_start(int b) { return (b * kN) / kG; }

struct Params {
    const unsigned char* ea;
    const int* src;
    const int* dst;
    unsigned char* out;
    unsigned char* tab;
    uint32_t* slots;
    unsigned* bar;
    CUtensorMap mx;
    CUtensorMap mg;
    CUtensorMap mc;
    CUtensorMap mv;
    CUtensorMap mu;
    CUtensorMap ms;
};

__global__ void __launch_bounds__(kThreads, 1) egc_kernel(const __grid_constant__ Params p) {
    extern __shared__ __align__(1024) unsigned char smem[];
    const uint32_t sb = smem_u32(smem);
    const int tid = threadIdx.x, warp = tid >> 5, lane = tid & 31;
    const int b = blockIdx.x;
    const int n0 = node_start(b), n1 = node_start(b + 1);
    const int nb = n0 & ~7;

    if (warp == 0) PROF(0);
    const int e0 = b * kEPB;
    const int nq = (min(kEPB, kE - e0)) >> 2;
    int4 d4, s4;
    if (tid < nq) {
        d4 = __ldg(reinterpret_cast<const int4*>(p.dst + e0) + tid);
        s4 = __ldg(reinterpret_cast<const int4*>(p.src + e0) + tid);
    }
    unsigned target = 0;
    if (tid == 288 || tid == 256) {
        asm volatile("ld.relaxed.gpu.global.u32 %0, [%1];" : "=r"(target) : "l"(p.bar + (tid == 256 ? 32 : 0)) : "memory");
        target = (target / kG + 1) * kG;
    }
    if (warp == 11) {
        if (lane < 6) asm volatile("prefetch.tensormap [%0];" ::"l"(&p.mx + lane) : "memory");
        if (lane == 0) {
#pragma unroll
            for (int i = 0; i < 5; ++i) mbar_init(sb + SM_MBAR + i * 8, 1);
            asm volatile("fence.mbarrier_init.release.cluster;" ::: "memory");
        }
        __syncwarp();
        named_arrive(4, 384);
        if (lane == 0) {
            mbar_expect(sb + SM_MBAR, 22528 + 32768);
            mbar_expect(sb + SM_MBAR + 8, 32768);
            mbar_expect(sb + SM_MBAR + 16, 32768 + 4096);
            mbar_expect(sb + SM_MBAR + 24, 32768);
#pragma unroll 1
            for (int h = 0; h < 2; ++h) {
                tma_load(sb + SM_X + h * 11264, &p.mx, h * 64, nb, sb + SM_MBAR);
                tma_load(sb + SM_W0 + h * 16384, &p.mg, h * 64, 128, sb + SM_MBAR);
            }
#pragma unroll 1
            for (int h = 0; h < 2; ++h) tma_load(sb + SM_W0 + 32768 + h * 16384, &p.mv, h * 64, 0, sb + SM_MBAR + 8);
        }
    } else {
        if (tid < 128) sts32(sb + SM_NCNT + tid * 4, 0);
        else if (tid < 128 + kG) sts32(sb + SM_SCNT + (tid - 128) * 4, 0);
#pragma unroll 1
        for (int i = tid; i < kG * 8; i += 352) sts128(sb + SM_SLOT + i * 16, kSentinel, kSentinel, kSentinel, kSentinel);
        named_wait(4, 384);
    }
    if (tid < nq) {
        const int dd[4] = {d4.x, d4.y, d4.z, d4.w};
        const int ss[4] = {s4.x, s4.y, s4.z, s4.w};
        uint32_t db[4], rank[4];
#pragma unroll
        for (int u = 0; u < 4; ++u) {
            db[u] = ((dd[u] + 1) * kG - 1) / kN;
            rank[u] = atoms_inc(sb + SM_SCNT + db[u] * 4);
        }
#pragma unroll
        for (int u = 0; u < 4; ++u) {
            const uint32_t nl = dd[u] - (node_start(db[u]) & ~7);
            if (rank[u] < kSlot)
                sts32(sb + SM_SLOT + db[u] * 128 + rank[u] * 4, (uint32_t)ss[u] | ((uint32_t)(tid * 4 + u) << 14) | (nl << 25));
        }
    }
    if (warp < 10) named_sync<5, 320>();
    if (warp == 8) {
#pragma unroll 1
        for (int d = lane; d < kG; d += 32)
            if (lds32(sb + SM_SCNT + d * 4) > kSlot) sts32(sb + SM_SLOT + d * 128, kOverflow);
        __syncwarp();
        if (lane == 0) {
            fence_async_smem();
            bulk_store(p.slots + (size_t)b * kG * kSlot, sb + SM_SLOT, kG * 128);
            bulk_commit();
            asm volatile("cp.async.bulk.wait_group 0;" ::: "memory");
            grid_arrive(p.bar);
            PROF(4);
        }
    } else if (tid == 288) {
        grid_wait(p.bar, target);
        PROF(5);
        mbar_expect(sb + SM_MBAR + 32, kG * 128);
        tma_load(sb + SM_SLOT, &p.ms, b * kSlot, 0, sb + SM_MBAR + 32);
    } else if (tid == 352) {
        mbar_wait(sb + SM_MBAR, 0);
#pragma unroll 1
        for (int h = 0; h < 2; ++h) {
            tma_load(sb + SM_W4 + h * 16384, &p.mg, h * 64, 0, sb + SM_MBAR + 16);
            tma_load(sb + SM_WC + h * 2048, &p.mc, h * 64, 256, sb + SM_MBAR + 16);
            tma_load(sb + SM_W4 + 32768 + h * 16384, &p.mu, h * 64, 0, sb + SM_MBAR + 24);
        }
    }
    __syncwarp();
    const int q = lane >> 3, pp = lane & 7;
    uint32_t rec[11], rank[11];
    auto count = [&]() {
        mbar_wait(sb + SM_MBAR + 32, 0);
#pragma unroll
        for (int i = 0; i < 11; ++i) rec[i] = lds32(sb + SM_SLOT + (warp + kWarps * i) * 128 + lane * 4);
#pragma unroll
        for (int i = 0; i < 11; ++i) {
            const bool valid = (rec[i] & 0x3FFFu) < (uint32_t)kN;
            rank[i] = atoms_inc(sb + SM_NCNT + (valid ? (rec[i] >> 25) : 128 + lane) * 4);
        }
    };
    if (warp < 8) {
        const int wg = warp >> 2, w4 = warp & 3;
        const uint32_t xlo = ((sb + SM_X) >> 4) | 0x10000u;
        const uint32_t sw = wg * 128 + (((2 * w4 + (q & 1)) ^ pp) << 4);
#pragma unroll 1
        for (int pair = 0; pair < 4; ++pair) {
            const uint32_t wpair = sb + (pair < 2 ? SM_W0 : SM_W4 - 65536) + pair * 32768;
            mbar_wait(sb + SM_MBAR + pair * 8, 0);
            if (warp == 0 && pair == 0) PROF(1);

            float acc[44];
            const uint32_t alo = ((wpair + wg * 16384) >> 4) | 0x10000u;
            asm volatile("wgmma.fence.sync.aligned;" ::: "memory");
#pragma unroll
            for (int s = 0; s < 8; ++s)
                wgmma_m64n88k16(acc, make_desc(alo + s * 128), make_desc(xlo + (s >> 2) * 704 + (s & 3) * 2), s);
            asm volatile("wgmma.commit_group.sync.aligned;" ::: "memory");
            asm volatile("wgmma.wait_group.sync.aligned 0;" ::: "memory");
#pragma unroll
            for (int i = 0; i < 44; ++i) asm volatile("" : "+f"(acc[i])::"memory");
            named_sync<1, 256>();
            const uint32_t a0 = wpair + ((q >> 1) * 8 + pp) * 256 + sw;
#pragma unroll
            for (int i = 0; i < 10; i += 2)
                stsm4t(a0 + i * 2048, pack_bf16(acc[4 * i], acc[4 * i + 1]), pack_bf16(acc[4 * i + 2], acc[4 * i + 3]),
                       pack_bf16(acc[4 * i + 4], acc[4 * i + 5]), pack_bf16(acc[4 * i + 6], acc[4 * i + 7]));
            stsm2t(wpair + (80 + pp) * 256 + sw, pack_bf16(acc[40], acc[41]), pack_bf16(acc[42], acc[43]));
            if (pair < 2) named_arrive(9 + pair, 288);
            if (warp == 0) PROF(2 + (pair & 1) * 4 + (pair >> 1) * 11);

        }
    } else {
        if (warp == 8) {
#pragma unroll 1
            for (int pair = 0; pair < 2; ++pair) {
                named_wait(9 + pair, 288);
                if (lane == 0) {
                    fence_async_smem();
                    bulk_store(p.tab + (size_t)pair * kTab + (size_t)n0 * 256, sb + SM_W0 + pair * 32768 + (n0 - nb) * 256, (n1 - n0) * 256);
                    bulk_commit();
                }
            }
            if (lane == 0) {
                asm volatile("cp.async.bulk.wait_group 0;" ::: "memory");
                PROF(8);
                grid_arrive(p.bar + 32);
            }
            __syncwarp();
        } else if (warp == 10) {
            mbar_wait(sb + SM_MBAR + EGC_PF_BAR * 8, 0);
#pragma unroll 1
            for (int i = lane; i < nq; i += 32) asm volatile("prefetch.global.L2 [%0];" ::"l"(p.ea + (size_t)e0 * 32 + i * 128) : "memory");
        }
    }
    if (warp == 0) PROF(3);
    count();
    uint32_t wc[8][4];
    mbar_wait(sb + SM_MBAR + 16, 0);
#pragma unroll
    for (int T = 0; T < 8; ++T)
        ldsm4t(wc[T], sb + SM_WC + (T >> 2) * 2048 + ((q >> 1) * 8 + pp) * 128 + ((((q & 1) ^ pp) << 4) ^ ((2 * T & 7) << 4)));
    if (warp == 0) PROF(14);
    __syncthreads();

    const int g = lane >> 2, t = lane & 3;
    int a0, a1;
    bool slow;
    {
        uint4 c = make_uint4(0, 0, 0, 0);
        if (lane < 22) c = lds128(sb + SM_NCNT + lane * 16);
        const uint32_t ovf = lds32(sb + SM_NCNT + 126 * 4);
        if (warp == 0) PROFB(9);
        const uint32_t s1 = c.x + c.y, s2 = s1 + c.z, s3 = s2 + c.w;
        uint32_t inc = s3;
#pragma unroll
        for (int o = 1; o < 32; o <<= 1) {
            const uint32_t v = __shfl_up_sync(0xffffffffu, inc, o);
            if (lane >= o) inc += v;
        }
        const uint32_t ex = inc - s3;
        const uint32_t total = __shfl_sync(0xffffffffu, inc, 31);
        if (lane < 24) sts128(sb + SM_P + lane * 16, ex, ex + c.x, ex + s1, ex + s2);
        slow = total > (uint32_t)kLCap || ovf != 0;
        __syncwarp();
        const uint32_t cb = warp * (kEPB * 32);
#pragma unroll
        for (int i = 0; i < 11; ++i) rank[i] += lds32(sb + SM_P + min(rec[i] >> 25, 95u) * 4);
#pragma unroll
        for (int i = 0; i < 11; ++i) {
            if ((rec[i] & 0x3FFFu) < (uint32_t)kN && !slow) sts64(sb + SM_LIST + rank[i] * 8, rec[i], cb + i * (kWarps * kEPB * 32));
        }
        const uint32_t m0 = 2 * ex + c.x, m1 = 2 * (ex + c.x) + c.y, m2 = 2 * (ex + s1) + c.z, m3 = 2 * (ex + s2) + c.w;
        const uint32_t t0 = (total * warp) / (kWarps / 2), t1 = (total * (warp + 1)) / (kWarps / 2);
        uint32_t kk = 0;
        if (lane < 22)
            kk = (m0 < t0) + (m1 < t0) + (m2 < t0) + (m3 < t0) + (((m0 < t1) + (m1 < t1) + (m2 < t1) + (m3 < t1)) << 16);
        kk = __reduce_add_sync(0xffffffffu, kk);
        const int lo = n0 - nb, hi = n1 - nb;
        a0 = warp == 0 ? lo : min(max((int)(kk & 0xFFFF), lo), hi);
        a1 = warp == kWarps - 1 ? hi : min(max((int)(kk >> 16), lo), hi);
        if (slow) {
            a0 = min(lo + 8 * warp, hi);
            a1 = min(a0 + 8, hi);
        }
        if (warp == 0) PROF(10);
        if (tid == 256) grid_wait(p.bar + 32, target);
        __syncthreads();
    }

    const uint32_t ident = (g == 2 * t) ? 0x00003F00u : ((g == 2 * t + 1) ? 0x3F000000u : 0u);
    const uint32_t xa = (pp ^ q) << 4;
    const uint32_t lrd = pp * 128 + ((q ^ pp) << 4);
    const uint32_t ring = sb + SM_RING + warp * (2 * kRingSlot);
    const unsigned char* ea_base = p.ea + t * 8;
    if (warp == 0) PROFB(12);
#pragma unroll 1
    for (int ws = a0; ws < a1;) {
        const int we = min(ws + 8, a1);
        uint32_t at[8][2];
        float agg[8][4];
        {
            const int row = min(ws + pp, kRows - 1);
            const uint32_t ra = sb + SM_W4 + row * 256;
#pragma unroll
            for (int u = 0; u < 4; ++u) {
                const uint32_t o = (u >> 1) * 128 + (((4 * (u & 1) + q) ^ (row & 7)) << 4);
                uint32_t r[4];
                ldsm4t(r, ra + o);
                at[2 * u][0] = r[0]; at[2 * u][1] = r[1]; at[2 * u + 1][0] = r[2]; at[2 * u + 1][1] = r[3];
                ldsm4t(r, ra + 32768 + o);
                mma16z(agg[2 * u], r[0], r[1], r[0], r[1], ident, ident);
                mma16z(agg[2 * u + 1], r[2], r[3], r[2], r[3], ident, ident);
            }
        }
        const uint32_t nlb = ws + 2 * t;
        int scan_pos = 0;
        do {
            int beg, end;
            uint32_t lbase;
            if (!slow) {
                beg = lds32(sb + SM_P + ws * 4);
                end = lds32(sb + SM_P + we * 4);
                lbase = sb + SM_LIST;
            } else {
                lbase = sb + SM_LIST + warp * (kLCap / kWarps) * 8;
                beg = 0;
                end = 0;
#pragma unroll 1
                while (scan_pos < kE && end <= kLCap / kWarps - 32) {
                    const int e = scan_pos + lane;
                    const int d = e < kE ? __ldg(p.dst + e) - nb : -1;
                    const bool m = d >= ws && d < we;
                    const unsigned bal = __ballot_sync(0xffffffffu, m);
                    if (m) sts64(lbase + (end + __popc(bal & ((1u << lane) - 1))) * 8, (uint32_t)__ldg(p.src + e) | ((uint32_t)d << 25), (uint32_t)e * 32);
                    end += __popc(bal);
                    scan_pos += 32;
                }
                __syncwarp();
            }
            const int nsteps = (end - beg + 7) >> 3;
#pragma unroll 1
            for (int k = -1; k < nsteps; ++k) {
                if (k + 1 < nsteps) {
                    const int idx = beg + (k + 1) * 8;
                    const uint32_t slot = ring + ((k + 1) & 1) * kRingSlot;
                    const bool va = idx + q < end, vb = idx + 4 + q < end, vy = idx + g < end;
                    uint32_t wa = 0, wb = 0, wy = 0, cb = 0;
                    if (va) wa = lds32(lbase + (idx + q) * 8);
                    if (vb) wb = lds32(lbase + (idx + 4 + q) * 8);
                    if (vy) {
                        wy = lds32(lbase + (idx + g) * 8);
                        cb = lds32(lbase + (idx + g) * 8 + 4);
                    }
                    const unsigned char* pa = p.tab + (((wa & 0x3FFFu) << 8) | (((wa << 4) & 0x70u) ^ xa));
                    const unsigned char* pb = p.tab + (((wb & 0x3FFFu) << 8) | (((wb << 4) & 0x70u) ^ xa ^ 64u));
                    const uint32_t d = slot + lane * 16, na = va ? 16 : 0, nb2 = vb ? 16 : 0;
                    cp16z(d, pa, na);
                    cp16z(d + 2048, pa + kTab, na);
                    cp16z(d + 512, pb, nb2);
                    cp16z(d + 2560, pb + kTab, nb2);
                    cp16z(d + 1024, pa + 128, na);
                    cp16z(d + 3072, pa + kTab + 128, na);
                    cp16z(d + 1536, pb + 128, nb2);
                    cp16z(d + 3584, pb + kTab + 128, nb2);
                    cp8z(slot + 4096 + lane * 8, ea_base + cb + ((wy >> 9) & 0xFFE0u), vy ? 8 : 0);
                }
                cp_commit();
                if (k < 0) continue;
                const uint32_t slot = ring + (k & 1) * kRingSlot;
                uint32_t wy = kPadRec;
                if (beg + k * 8 + g < end) wy = lds32(lbase + (beg + k * 8 + g) * 8);
                cp_wait<1>();
                __syncwarp();
                uint32_t ea0, ea1;
                asm volatile("ldmatrix.sync.aligned.m8n8.x2.shared.b16 {%0,%1}, [%2];" : "=r"(ea0), "=r"(ea1) : "r"(slot + 4096 + pp * 32 + (q & 1) * 16) : "memory");
                ea0 = hfma2(ea0, 0x3F003F00u, 0x80008000u);
                ea1 = hfma2(ea1, 0x3F003F00u, 0x80008000u);
                const uint32_t dd = (wy >> 25) - nlb;
                const uint32_t sT = dd == 0 ? 0x00003F00u : (dd == 1 ? 0x3F000000u : 0u);
                const uint32_t sA = movm_t(sT);
#pragma unroll
                for (int u = 0; u < 4; ++u) {
                    uint32_t bq[4], vq[4];
                    const uint32_t la = slot + ((u & 1) ? (lrd ^ 64u) : lrd) + (u >> 1) * 1024;
                    ldsm4(bq, la);
                    ldsm4t(vq, la + 2048);
#pragma unroll
                    for (int s = 0; s < 2; ++s) {
                        const int T = 2 * u + s;
                        float z[4];
                        mma16z(z, wc[T][0], wc[T][1], wc[T][2], wc[T][3], ea0, ea1);
                        mma8(z, at[T][0], at[T][1], sT);
                        mma16(z, ident, 0u, 0u, ident, bq[2 * s], bq[2 * s + 1]);
                        const uint32_t t01 = pack_bf16(tanh_fast(z[0]), tanh_fast(z[1]));
                        const uint32_t t23 = pack_bf16(tanh_fast(z[2]), tanh_fast(z[3]));
                        mma8(agg[T], hfma2(vq[2 * s], t01, vq[2 * s]), hfma2(vq[2 * s + 1], t23, vq[2 * s + 1]), sA);
                    }
                }
                __syncwarp();
            }
            cp_wait<0>();
        } while (slow && scan_pos < kE);

        {
            const uint32_t st = sb + SM_OUT + warp * 2048;
#pragma unroll
            for (int u = 0; u < 4; ++u) {
                uint32_t pk[4];
#pragma unroll
                for (int j = 0; j < 4; ++j) {
                    const float h0 = 0.5f * agg[2 * u + (j >> 1)][2 * (j & 1)], h1 = 0.5f * agg[2 * u + (j >> 1)][2 * (j & 1) + 1];
                    pk[j] = pack_bf16(fmaf(h0, tanh_fast(h0), h0), fmaf(h1, tanh_fast(h1), h1));
                }
                stsm4t(st + pp * 256 + (u >> 1) * 128 + (((4 * (u & 1) + q) ^ pp) << 4), pk[0], pk[1], pk[2], pk[3]);
            }
            __syncwarp();
#pragma unroll 1
            for (int r = lane >> 4; r < we - ws; r += 2) {
                const int c = lane & 15;
                const uint4 v = lds128(st + r * 256 + (c >> 3) * 128 + (((c & 7) ^ r) << 4));
                *reinterpret_cast<uint4*>(p.out + (size_t)(nb + ws + r) * 256 + c * 16) = v;
            }
            __syncwarp();
        }
        ws = we;
    }
    if (warp == 0) PROF(11);
}

}

typedef CUresult (*EncodeTiledFn)(CUtensorMap*, CUtensorMapDataType, cuuint32_t, void*, const cuuint64_t*, const cuuint64_t*,
                                  const cuuint32_t*, const cuuint32_t*, CUtensorMapInterleave, CUtensorMapSwizzle,
                                  CUtensorMapL2promotion, CUtensorMapFloatOOBfill);

static void encode_map(EncodeTiledFn enc, CUtensorMap* m, const void* base, int rows, int box_rows) {
    const cuuint64_t dims[2] = {128, (cuuint64_t)rows};
    const cuuint64_t strides[1] = {256};
    const cuuint32_t box[2] = {64, (cuuint32_t)box_rows};
    const cuuint32_t estr[2] = {1, 1};
    enc(m, CU_TENSOR_MAP_DATA_TYPE_BFLOAT16, 2, const_cast<void*>(base), dims, strides, box, estr, CU_TENSOR_MAP_INTERLEAVE_NONE,
        CU_TENSOR_MAP_SWIZZLE_128B, CU_TENSOR_MAP_L2_PROMOTION_L2_256B, CU_TENSOR_MAP_FLOAT_OOB_FILL_NONE);
}

extern "C" void kernel_launch(void* const* d_in, const int* in_sizes, int n_in, void* d_out, int out_size) {
    (void)in_sizes; (void)n_in; (void)out_size;
    static EncodeTiledFn enc = nullptr;
    if (!enc) {
        cudaFuncSetAttribute(egc::egc_kernel, cudaFuncAttributeMaxDynamicSharedMemorySize, egc::SM_TOTAL);
        void* fn = nullptr;
        cudaDriverEntryPointQueryResult qr;
        cudaGetDriverEntryPoint("cuTensorMapEncodeTiled", &fn, cudaEnableDefault, &qr);
        enc = (EncodeTiledFn)fn;
    }
    static void *slots_addr = nullptr, *tab_addr = nullptr, *bar_addr = nullptr;
    if (!slots_addr) {
        cudaGetSymbolAddress(&slots_addr, egc::g_slots);
        cudaGetSymbolAddress(&tab_addr, egc::g_T);
        cudaGetSymbolAddress(&bar_addr, egc::g_bar);
    }
    egc::Params p;
    p.tab = (unsigned char*)tab_addr;
    p.slots = (uint32_t*)slots_addr;
    p.bar = (unsigned*)bar_addr;
    {
        const cuuint64_t dims[2] = {egc::kG * egc::kSlot, egc::kG};
        const cuuint64_t strides[1] = {egc::kG * egc::kSlot * 4};
        const cuuint32_t box[2] = {egc::kSlot, egc::kG};
        const cuuint32_t estr[2] = {1, 1};
        enc(&p.ms, CU_TENSOR_MAP_DATA_TYPE_UINT32, 2, slots_addr, dims, strides, box, estr, CU_TENSOR_MAP_INTERLEAVE_NONE,
            CU_TENSOR_MAP_SWIZZLE_NONE, CU_TENSOR_MAP_L2_PROMOTION_NONE, CU_TENSOR_MAP_FLOAT_OOB_FILL_NONE);
    }
    encode_map(enc, &p.mx, d_in[0], egc::kN, egc::kRows);
    encode_map(enc, &p.mg, d_in[6], 272, 128);
    encode_map(enc, &p.mc, d_in[6], 272, 16);
    encode_map(enc, &p.mv, d_in[5], 128, 128);
    encode_map(enc, &p.mu, d_in[4], 128, 128);
    p.ea = (const unsigned char*)d_in[1];
    p.src = (const int*)d_in[2];
    p.dst = (const int*)d_in[3];
    p.out = (unsigned char*)d_out;
    egc::egc_kernel<<<egc::kG, egc::kThreads, egc::SM_TOTAL, cudaStreamPerThread>>>(p);
}
```

```cpp
#include <cuda_runtime.h>
#include <cuda.h>
#include <cuda_bf16.h>
#include <stdint.h>

#define EGC_PF_BAR 1
namespace egc {

constexpr int kN = 10000;
constexpr int kE = 160000;
constexpr int kG = 132;
constexpr int kEPB = 1216;
constexpr int kWarps = 12;
constexpr int kThreads = kWarps * 32;
constexpr int kSlot = 32;
constexpr int kRows = 80;
constexpr int kNGrp = 10;
constexpr int kGCap = 192;
constexpr uint32_t kTab = kN * 256;
constexpr uint32_t kSentinel = 0xFFFFFFFFu;
constexpr uint32_t kOverflow = 126u << 25;
constexpr uint32_t kPadRec = 127u << 25;
constexpr int kSpinLimit = 1 << 22;
constexpr int kRingSlot = 4352;

static_assert(kN % 8 == 0 && kN < 16382, "src must fit 14 bits");
static_assert(kEPB * kG >= kE && kEPB <= 2048 && kEPB % 4 == 0 && kE % 4 == 0, "edge chunks");
static_assert(kG % kWarps == 0, "slot lines per warp");

constexpr int SM_X = 0;
constexpr int SM_W0 = 22528;
constexpr int SM_SLOT = SM_W0 + 4 * 16384;
constexpr int SM_RING = 0;
constexpr int SM_W4 = 105472;
constexpr int SM_WC = SM_W4 + 4 * 16384;
constexpr int SM_LIST = SM_WC + 4096;
constexpr int SM_EXP = SM_LIST + kNGrp * kGCap * 8;
constexpr int SM_NCNT = SM_EXP + 7 * 4096;
constexpr int SM_SCNT = SM_NCNT + 192;
constexpr int SM_MBAR = SM_SCNT + 544;
constexpr int SM_PROF = SM_MBAR + 17 * 8 + 8;
constexpr int SM_TOTAL = SM_PROF + 80;
static_assert(SM_SLOT + kG * 128 <= SM_W4 && kWarps * 2 * kRingSlot <= SM_W4, "smem map");
static_assert(SM_W0 % 1024 == 0 && SM_W4 % 1024 == 0 && SM_WC % 1024 == 0 && SM_TOTAL <= 232448, "smem map");

__device__ __align__(1024) unsigned char g_T[2 * kTab];
__device__ __align__(1024) uint32_t g_slots[kG * kG * kSlot];
__device__ unsigned g_bar[64];
#define PROF(i)
#define PROFB(i)

__device__ __forceinline__ uint32_t smem_u32(const void* p) { return (uint32_t)__cvta_generic_to_shared(p); }
__device__ __forceinline__ void cp16(uint32_t dst, const void* src) {
    asm volatile("cp.async.cg.shared.global [%0], [%1], 16;" ::"r"(dst), "l"(src) : "memory");
}
__device__ __forceinline__ void cp16z(uint32_t dst, const void* src, uint32_t nbytes) {
    asm volatile("cp.async.cg.shared.global [%0], [%1], 16, %2;" ::"r"(dst), "l"(src), "r"(nbytes) : "memory");
}
__device__ __forceinline__ void cp8z(uint32_t dst, const void* src, uint32_t nbytes) {
    asm volatile("cp.async.ca.shared.global [%0], [%1], 8, %2;" ::"r"(dst), "l"(src), "r"(nbytes) : "memory");
}
__device__ __forceinline__ void named_arrive(int id, int n) { asm volatile("bar.arrive %0, %1;" ::"r"(id), "r"(n) : "memory"); }
__device__ __forceinline__ void named_wait(int id, int n) { asm volatile("bar.sync %0, %1;" ::"r"(id), "r"(n) : "memory"); }
__device__ __forceinline__ void grid_arrive(unsigned* ctr) {
    asm volatile("red.relaxed.gpu.global.add.u32 [%0], 1;" ::"l"(ctr) : "memory");
}
__device__ __forceinline__ void grid_wait(const unsigned* ctr, unsigned target) {
    unsigned v = 0;
    for (int it = 0; it < kSpinLimit; ++it) {
        asm volatile("ld.relaxed.gpu.global.u32 %0, [%1];" : "=r"(v) : "l"(ctr) : "memory");
        if ((int)(v - target) >= 0) break;
    }
}
__device__ __forceinline__ void cp_commit() { asm volatile("cp.async.commit_group;" ::: "memory"); }
template <int NPEND> __device__ __forceinline__ void cp_wait() { asm volatile("cp.async.wait_group %0;" ::"n"(NPEND) : "memory"); }
__device__ __forceinline__ void fence_async_smem() { asm volatile("fence.proxy.async.shared::cta;" ::: "memory"); }
template <int ID, int N> __device__ __forceinline__ void named_sync() { asm volatile("bar.sync %0, %1;" ::"n"(ID), "n"(N) : "memory"); }
__device__ __forceinline__ void bulk_store(void* gdst, uint32_t ssrc, uint32_t bytes) {
    asm volatile("cp.async.bulk.global.shared::cta.bulk_group [%0], [%1], %2;" ::"l"(gdst), "r"(ssrc), "r"(bytes) : "memory");
}
__device__ __forceinline__ void bulk_commit() { asm volatile("cp.async.bulk.commit_group;" ::: "memory"); }
__device__ __forceinline__ void mbar_init(uint32_t bar, uint32_t cnt) {
    asm volatile("mbarrier.init.shared::cta.b64 [%0], %1;" ::"r"(bar), "r"(cnt) : "memory");
}
__device__ __forceinline__ void mbar_expect(uint32_t bar, uint32_t bytes) {
    asm volatile("mbarrier.arrive.expect_tx.shared::cta.b64 _, [%0], %1;" ::"r"(bar), "r"(bytes) : "memory");
}
__device__ __forceinline__ void tma_load(uint32_t dst, const CUtensorMap* map, int col, int row, uint32_t bar) {
    asm volatile("cp.async.bulk.tensor.2d.shared::cluster.global.mbarrier::complete_tx::bytes [%0], [%1, {%3, %4}], [%2];"
                 ::"r"(dst), "l"(map), "r"(bar), "r"(col), "r"(row) : "memory");
}
__device__ __forceinline__ void mbar_arrive(uint32_t bar) {
    asm volatile("mbarrier.arrive.shared::cta.b64 _, [%0];" ::"r"(bar) : "memory");
}
__device__ __forceinline__ void mbar_wait(uint32_t bar, uint32_t parity) {
    asm volatile(
        "{\n"
        ".reg .pred p, q;\n"
        ".reg .u32 n;\n"
        "mov.u32 n, %2;\n"
        "WAIT_LOOP:\n"
        "mbarrier.try_wait.parity.shared::cta.b64 p, [%0], %1;\n"
        "sub.u32 n, n, 1;\n"
        "setp.ne.and.u32 q, n, 0, !p;\n"
        "@q bra WAIT_LOOP;\n"
        "}\n" ::"r"(bar), "r"(parity), "n"(kSpinLimit) : "memory");
}
__device__ __forceinline__ uint32_t lds32(uint32_t a) {
    uint32_t v;
    asm volatile("ld.shared.u32 %0, [%1];" : "=r"(v) : "r"(a) : "memory");
    return v;
}
__device__ __forceinline__ uint4 lds128(uint32_t a) {
    uint4 v;
    asm volatile("ld.shared.v4.u32 {%0,%1,%2,%3}, [%4];" : "=r"(v.x), "=r"(v.y), "=r"(v.z), "=r"(v.w) : "r"(a) : "memory");
    return v;
}
__device__ __forceinline__ void sts32(uint32_t a, uint32_t v) { asm volatile("st.shared.u32 [%0], %1;" ::"r"(a), "r"(v) : "memory"); }
__device__ __forceinline__ void sts64(uint32_t a, uint32_t x, uint32_t y) {
    asm volatile("st.shared.v2.u32 [%0], {%1,%2};" ::"r"(a), "r"(x), "r"(y) : "memory");
}
__device__ __forceinline__ void sts128(uint32_t a, uint32_t x, uint32_t y, uint32_t z, uint32_t w) {
    asm volatile("st.shared.v4.u32 [%0], {%1,%2,%3,%4};" ::"r"(a), "r"(x), "r"(y), "r"(z), "r"(w) : "memory");
}
__device__ __forceinline__ uint32_t atoms_inc(uint32_t a) {
    uint32_t old;
    asm volatile("atom.shared.add.u32 %0, [%1], 1;" : "=r"(old) : "r"(a) : "memory");
    return old;
}

__device__ __forceinline__ void ldsm4(uint32_t (&r)[4], uint32_t a) {
    asm volatile("ldmatrix.sync.aligned.m8n8.x4.shared.b16 {%0,%1,%2,%3}, [%4];"
                 : "=r"(r[0]), "=r"(r[1]), "=r"(r[2]), "=r"(r[3]) : "r"(a) : "memory");
}
__device__ __forceinline__ void ldsm4t(uint32_t (&r)[4], uint32_t a) {
    asm volatile("ldmatrix.sync.aligned.m8n8.x4.trans.shared.b16 {%0,%1,%2,%3}, [%4];"
                 : "=r"(r[0]), "=r"(r[1]), "=r"(r[2]), "=r"(r[3]) : "r"(a) : "memory");
}
__device__ __forceinline__ void stsm4t(uint32_t a, uint32_t r0, uint32_t r1, uint32_t r2, uint32_t r3) {
    asm volatile("stmatrix.sync.aligned.m8n8.x4.trans.shared.b16 [%0], {%1,%2,%3,%4};" ::"r"(a), "r"(r0), "r"(r1), "r"(r2), "r"(r3) : "memory");
}
__device__ __forceinline__ void stsm2t(uint32_t a, uint32_t r0, uint32_t r1) {
    asm volatile("stmatrix.sync.aligned.m8n8.x2.trans.shared.b16 [%0], {%1,%2};" ::"r"(a), "r"(r0), "r"(r1) : "memory");
}
__device__ __forceinline__ uint32_t pack_bf16(float lo, float hi) {
    uint32_t r;
    asm("cvt.rn.bf16x2.f32 %0, %1, %2;" : "=r"(r) : "f"(hi), "f"(lo));
    return r;
}
__device__ __forceinline__ uint32_t hfma2(uint32_t a, uint32_t b, uint32_t c) {
    uint32_t d;
    asm("fma.rn.bf16x2 %0, %1, %2, %3;" : "=r"(d) : "r"(a), "r"(b), "r"(c));
    return d;
}
__device__ __forceinline__ float tanh_fast(float x) {
    float r;
    asm("tanh.approx.f32 %0, %1;" : "=f"(r) : "f"(x));
    return r;
}
__device__ __forceinline__ void mma16z(float* d, uint32_t a0, uint32_t a1, uint32_t a2, uint32_t a3, uint32_t b0, uint32_t b1) {
    asm("mma.sync.aligned.m16n8k16.row.col.f32.bf16.bf16.f32 {%0,%1,%2,%3}, {%4,%5,%6,%7}, {%8,%9}, {%10,%10,%10,%10};"
        : "=f"(d[0]), "=f"(d[1]), "=f"(d[2]), "=f"(d[3])
        : "r"(a0), "r"(a1), "r"(a2), "r"(a3), "r"(b0), "r"(b1), "f"(0.f));
}
__device__ __forceinline__ void mma16(float* d, uint32_t a0, uint32_t a1, uint32_t a2, uint32_t a3, uint32_t b0, uint32_t b1) {
    asm("mma.sync.aligned.m16n8k16.row.col.f32.bf16.bf16.f32 {%0,%1,%2,%3}, {%4,%5,%6,%7}, {%8,%9}, {%0,%1,%2,%3};"
        : "+f"(d[0]), "+f"(d[1]), "+f"(d[2]), "+f"(d[3])
        : "r"(a0), "r"(a1), "r"(a2), "r"(a3), "r"(b0), "r"(b1));
}
__device__ __forceinline__ void mma8(float* d, uint32_t a0, uint32_t a1, uint32_t b0) {
    asm("mma.sync.aligned.m16n8k8.row.col.f32.bf16.bf16.f32 {%0,%1,%2,%3}, {%4,%5}, {%6}, {%0,%1,%2,%3};"
        : "+f"(d[0]), "+f"(d[1]), "+f"(d[2]), "+f"(d[3])
        : "r"(a0), "r"(a1), "r"(b0));
}
__device__ __forceinline__ uint32_t movm_t(uint32_t a) {
    uint32_t d;
    asm("movmatrix.sync.aligned.m8n8.trans.b16 %0, %1;" : "=r"(d) : "r"(a));
    return d;
}

__device__ __forceinline__ uint64_t make_desc(uint32_t lo) {
    uint64_t d;
    asm("mov.b64 %0, {%1, %2};" : "=l"(d) : "r"(lo), "r"(0x40000040u));
    return d;
}
__device__ __forceinline__ void wgmma_m64n80k16(float (&d)[40], uint64_t da, uint64_t db, int scale_d) {
    asm volatile(
        "{.reg .pred p; setp.ne.b32 p, %42, 0;\n"
        "wgmma.mma_async.sync.aligned.m64n80k16.f32.bf16.bf16 "
        "{%0,%1,%2,%3,%4,%5,%6,%7,%8,%9,%10,%11,%12,%13,%14,%15,%16,%17,%18,%19,"
        "%20,%21,%22,%23,%24,%25,%26,%27,%28,%29,%30,%31,%32,%33,%34,%35,%36,%37,%38,%39},"
        " %40, %41, p, 1, 1, 1, 0;}\n"
        : "+f"(d[0]), "+f"(d[1]), "+f"(d[2]), "+f"(d[3]), "+f"(d[4]), "+f"(d[5]), "+f"(d[6]), "+f"(d[7]),
          "+f"(d[8]), "+f"(d[9]), "+f"(d[10]), "+f"(d[11]), "+f"(d[12]), "+f"(d[13]), "+f"(d[14]), "+f"(d[15]),
          "+f"(d[16]), "+f"(d[17]), "+f"(d[18]), "+f"(d[19]), "+f"(d[20]), "+f"(d[21]), "+f"(d[22]), "+f"(d[23]),
          "+f"(d[24]), "+f"(d[25]), "+f"(d[26]), "+f"(d[27]), "+f"(d[28]), "+f"(d[29]), "+f"(d[30]), "+f"(d[31]),
          "+f"(d[32]), "+f"(d[33]), "+f"(d[34]), "+f"(d[35]), "+f"(d[36]), "+f"(d[37]), "+f"(d[38]), "+f"(d[39])
        : "l"(da), "l"(db), "r"(scale_d));
}

__device__ __forceinline__ int node_start(int b) { return (b * kN) / kG; }
__device__ __forceinline__ uint32_t exp_slot(uint32_t sb, int w) {
    return w <= 4 ? sb + SM_W4 + 22528 + ((w - 1) >> 1) * 32768 + ((w - 1) & 1) * 4096 : sb + SM_EXP + (w - 5) * 4096;
}

struct Params {
    const unsigned char* ea;
    const int* src;
    const int* dst;
    unsigned char* out;
    unsigned char* tab;
    uint32_t* slots;
    unsigned* bar;
    CUtensorMap mx;
    CUtensorMap mg;
    CUtensorMap mc;
    CUtensorMap mv;
    CUtensorMap mu;
    CUtensorMap ms;
};

__global__ void __launch_bounds__(kThreads, 1) egc_kernel(const __grid_constant__ Params p) {
    extern __shared__ __align__(1024) unsigned char smem[];
    const uint32_t sb = smem_u32(smem);
    const int tid = threadIdx.x, warp = tid >> 5, lane = tid & 31;
    const int b = blockIdx.x;
    const int n0 = node_start(b), n1 = node_start(b + 1);
    const int nb = n0;

    if (warp == 0) PROF(0);
    const int e0 = b * kEPB;
    const int nq = (min(kEPB, kE - e0)) >> 2;
    int4 d4, s4;
    if (tid < nq) {
        d4 = __ldg(reinterpret_cast<const int4*>(p.dst + e0) + tid);
        s4 = __ldg(reinterpret_cast<const int4*>(p.src + e0) + tid);
    }
    unsigned target = 0;
    if (tid == 288 || tid == 256) {
        asm volatile("ld.relaxed.gpu.global.u32 %0, [%1];" : "=r"(target) : "l"(p.bar + (tid == 256 ? 32 : 0)) : "memory");
        target = (target / kG + 1) * kG;
    }
    if (warp == 11) {
        if (lane < 6) asm volatile("prefetch.tensormap [%0];" ::"l"(&p.mx + lane) : "memory");
        if (lane == 0) {
#pragma unroll
            for (int i = 0; i < 5; ++i) mbar_init(sb + SM_MBAR + i * 8, 1);
            asm volatile("fence.mbarrier_init.release.cluster;" ::: "memory");
        }
        __syncwarp();
        named_arrive(4, 384);
        if (lane == 0) {
            mbar_expect(sb + SM_MBAR, 20480 + 32768);
            tma_load(sb + SM_X, &p.mx, 0, nb, sb + SM_MBAR);
            tma_load(sb + SM_X + 10240, &p.mx, 64, nb, sb + SM_MBAR);
            tma_load(sb + SM_W0, &p.mg, 0, 128, sb + SM_MBAR);
            tma_load(sb + SM_W0 + 16384, &p.mg, 64, 128, sb + SM_MBAR);
            mbar_expect(sb + SM_MBAR + 8, 32768);
            tma_load(sb + SM_W0 + 32768, &p.mv, 0, 0, sb + SM_MBAR + 8);
            tma_load(sb + SM_W0 + 49152, &p.mv, 64, 0, sb + SM_MBAR + 8);
            mbar_expect(sb + SM_MBAR + 16, 32768 + 4096);
            mbar_expect(sb + SM_MBAR + 24, 32768);
        }
        __syncwarp();
    } else {
        if (tid < 16) sts32(sb + SM_NCNT + tid * 4, 0);
        else if (tid >= 320 && tid < 320 + kWarps) mbar_init(sb + SM_MBAR + 40 + (tid - 320) * 8, 1);
        else if (tid >= 128 && tid < 128 + kG) sts32(sb + SM_SCNT + (tid - 128) * 4, 0);
#pragma unroll 1
        for (int i = tid; i < kG * 8; i += 352) sts128(sb + SM_SLOT + i * 16, kSentinel, kSentinel, kSentinel, kSentinel);
        named_wait(4, 384);
    }
    if (tid < nq) {
        const int dd[4] = {d4.x, d4.y, d4.z, d4.w};
        const int ss[4] = {s4.x, s4.y, s4.z, s4.w};
        uint32_t db[4], rank[4];
#pragma unroll
        for (int u = 0; u < 4; ++u) {
            db[u] = ((dd[u] + 1) * kG - 1) / kN;
            rank[u] = atoms_inc(sb + SM_SCNT + db[u] * 4);
        }
#pragma unroll
        for (int u = 0; u < 4; ++u) {
            const uint32_t nl = dd[u] - node_start(db[u]);
            if (rank[u] < kSlot)
                sts32(sb + SM_SLOT + db[u] * 128 + rank[u] * 4, (uint32_t)ss[u] | ((uint32_t)(tid * 4 + u) << 14) | (nl << 25));
        }
    }
    if (warp < 10) named_sync<5, 320>();
    if (warp == 8) {
#pragma unroll 1
        for (int d = lane; d < kG; d += 32)
            if (lds32(sb + SM_SCNT + d * 4) > kSlot) sts32(sb + SM_SLOT + d * 128, kOverflow);
        __syncwarp();
        if (lane == 0) {
            fence_async_smem();
            bulk_store(p.slots + (size_t)b * kG * kSlot, sb + SM_SLOT, kG * 128);
            bulk_commit();
            asm volatile("cp.async.bulk.wait_group 0;" ::: "memory");
            grid_arrive(p.bar);
            PROF(4);
        }
    } else if (tid == 288) {
        grid_wait(p.bar, target);
        PROF(5);
        mbar_expect(sb + SM_MBAR + 32, kG * 128);
        tma_load(sb + SM_SLOT, &p.ms, b * kSlot, 0, sb + SM_MBAR + 32);
    } else if (warp == 11) {
        mbar_wait(sb + SM_MBAR, 0);
        if (lane < 6) {
            const int h = lane & 1, m = lane >> 1;
            tma_load(sb + (m == 1 ? SM_WC + h * 2048 : SM_W4 + (m >> 1) * 32768 + h * 16384), m == 0 ? &p.mg : (m == 1 ? &p.mc : &p.mu),
                     h * 64, m == 1 ? 256 : 0, sb + SM_MBAR + (m == 2 ? 24 : 16));
        }
    }
    __syncwarp();
    const int q = lane >> 3, pp = lane & 7;
    if (warp < 8) {
        const int wg = warp >> 2, w4 = warp & 3;
        const uint32_t xlo = ((sb + SM_X) >> 4) | 0x10000u;
        const uint32_t sw = wg * 128 + (((2 * w4 + (q & 1)) ^ ((pp + n0) & 7)) << 4);
#pragma unroll 1
        for (int pair = 0; pair < 4; ++pair) {
            const uint32_t wpair = sb + (pair < 2 ? SM_W0 : SM_W4 - 65536) + pair * 32768;
            mbar_wait(sb + SM_MBAR + pair * 8, 0);
            if (warp == 0 && pair == 0) PROF(1);

            float acc[40];
            const uint32_t alo = ((wpair + wg * 16384) >> 4) | 0x10000u;
            asm volatile("wgmma.fence.sync.aligned;" ::: "memory");
#pragma unroll
            for (int s = 0; s < 8; ++s)
                wgmma_m64n80k16(acc, make_desc(alo + s * 128), make_desc(xlo + (s >> 2) * 640 + (s & 3) * 2), s);
            asm volatile("wgmma.commit_group.sync.aligned;" ::: "memory");
            asm volatile("wgmma.wait_group.sync.aligned 0;" ::: "memory");
#pragma unroll
            for (int i = 0; i < 40; ++i) asm volatile("" : "+f"(acc[i])::"memory");
            named_sync<1, 256>();
            const uint32_t a0 = wpair + ((q >> 1) * 8 + pp) * 256 + sw;
#pragma unroll
            for (int i = 0; i < 10; i += 2)
                stsm4t(a0 + i * 2048, pack_bf16(acc[4 * i], acc[4 * i + 1]), pack_bf16(acc[4 * i + 2], acc[4 * i + 3]),
                       pack_bf16(acc[4 * i + 4], acc[4 * i + 5]), pack_bf16(acc[4 * i + 6], acc[4 * i + 7]));
            if (pair < 2) named_arrive(9 + pair, 288);
            if (warp == 0) PROF(2 + (pair & 1) * 4 + (pair >> 1) * 11);

        }
    } else {
        if (warp == 8) {
#pragma unroll 1
            for (int pair = 0; pair < 2; ++pair) {
                named_wait(9 + pair, 288);
                if (lane == 0) {
                    fence_async_smem();
                    bulk_store(p.tab + (size_t)pair * kTab + (size_t)n0 * 256, sb + SM_W0 + pair * 32768 + (n0 - nb) * 256, (n1 - n0) * 256);
                    bulk_commit();
                }
            }
            if (lane == 0) {
                asm volatile("cp.async.bulk.wait_group 0;" ::: "memory");
                PROF(8);
                grid_arrive(p.bar + 32);
            }
            __syncwarp();
        } else if (warp == 10) {
            mbar_wait(sb + SM_MBAR + EGC_PF_BAR * 8, 0);
#pragma unroll 1
            for (int i = lane; i < nq; i += 32) asm volatile("prefetch.global.L2 [%0];" ::"l"(p.ea + (size_t)e0 * 32 + i * 128) : "memory");
        }
    }
    if (warp == 0) PROF(3);
    {
        const uint32_t c0 = 2 * warp + (lane >> 4);
        uint32_t off = (lane & 15) * 4;
        bool more;
        mbar_wait(sb + SM_MBAR + 32, 0);
#pragma unroll 1
        do {
            uint32_t rec[6], rank[6];
#pragma unroll
            for (int i = 0; i < 6; ++i) rec[i] = c0 + 24 * i < kG ? lds32(sb + SM_SLOT + (c0 + 24 * i) * 128 + off) : kSentinel;
            bool last = false;
#pragma unroll
            for (int i = 0; i < 6; ++i) {
                const bool valid = (rec[i] & 0x3FFFu) < (uint32_t)kN;
                last |= valid;
                rank[i] = atoms_inc(sb + SM_NCNT + (valid ? (rec[i] >> 28) : 16 + lane) * 4);
            }
#pragma unroll
            for (int i = 0; i < 6; ++i) {
                if (rank[i] < (uint32_t)kGCap && (rec[i] >> 28) < (uint32_t)kNGrp)
                    sts64(sb + SM_LIST + ((rec[i] >> 28) * kGCap + rank[i]) * 8, rec[i], (c0 + 24 * i) * (kEPB * 32));
            }
            more = off < 64 && __any_sync(0xffffffffu, last && (lane & 15) == 15);
            off += 64;
        } while (more);
    }
    if (warp == 0) PROF(10);
    if (tid == 256) grid_wait(p.bar + 32, target);
    __syncwarp();
    __syncthreads();

    const int g = lane >> 2, t = lane & 3;
    const int lo = n0 - nb, hi = n1 - nb;
    uint32_t cnt = lane < 16 ? lds32(sb + SM_NCNT + lane * 4) : 0;
    if (warp == 0) PROF(9);
    const bool slow = __any_sync(0xffffffffu, lane < kNGrp ? cnt > (uint32_t)kGCap : cnt != 0);
    const int ns = (lane < kNGrp && lane * 8 < hi) ? max(1, (int)(cnt + 7) >> 3) : 0;
    int sinc = ns;
#pragma unroll
    for (int o = 1; o < 16; o <<= 1) {
        const int v = __shfl_up_sync(0xffffffffu, sinc, o);
        if (lane >= o) sinc += v;
    }
    const int S = __shfl_sync(0xffffffffu, sinc, 15);
    const int k0 = (S * warp) / kWarps, k1 = (S * (warp + 1)) / kWarps;
    int sgrp = 0;
#pragma unroll
    for (int i = 0; i < kNGrp; ++i) sgrp += __shfl_sync(0xffffffffu, sinc, i) <= k0 + lane;
    sgrp = min(sgrp, kNGrp - 1);
    const int gtab = sinc | (ns << 16);
    uint32_t stab;
    {
        const int gt = __shfl_sync(0xffffffffu, gtab, sgrp);
        const int first = sgrp * kGCap + (k0 + lane - ((gt & 0xFFFF) - (gt >> 16))) * 8;
        stab = (first & 0xFFF) | ((sgrp * kGCap + __shfl_sync(0xffffffffu, (int)cnt, sgrp)) << 12) | (sgrp << 24);
    }
    int nsteps = k1 - k0;

    const uint32_t ident = (g == 2 * t) ? 0x00003F00u : ((g == 2 * t + 1) ? 0x3F000000u : 0u);
    const uint32_t xa = (pp ^ q) << 4;
    const uint32_t lrd = pp * 128 + ((q ^ pp) << 4);
    const uint32_t ring = sb + SM_RING + warp * (2 * kRingSlot);
    const uint32_t lbase = sb + SM_LIST;
    const unsigned char* ea_base = p.ea + t * 8;
    uint32_t wc[8][4], at[8][2];
    float agg[8][4];
    int scan_pos = 0;
    if (slow) {
        nsteps = (warp < kNGrp && warp * 8 < hi) ? 1 : 0;
        stab = warp << 24;
    }
    int k = -1;
    uint32_t st_c = 0;
#pragma unroll 1
    for (int ks = -1; ks < nsteps;) {
        int gc = 0, ke = 0, gend = 0;
        bool own = false;
        unsigned imp = 0;
        if (ks >= 0) {
            gc = __shfl_sync(0xffffffffu, stab, ks) >> 24;
            ke = ks + __popc(__ballot_sync(0xffffffffu, (int)(stab >> 24) == gc && lane >= ks && lane < nsteps));
            const int gt = __shfl_sync(0xffffffffu, gtab, gc);
            gend = gt & 0xFFFF;
            own = slow || gend - (gt >> 16) >= k0;
            if (own && !slow)
                imp = __ballot_sync(0xffffffffu, lane > warp && lane < kWarps && (S * lane) / kWarps < gend &&
                                                     (S * (lane + 1)) / kWarps != (S * lane) / kWarps);
            if (ks == 0) {
                mbar_wait(sb + SM_MBAR + 16, 0);
#pragma unroll
                for (int T = 0; T < 8; ++T)
                    ldsm4t(wc[T], sb + SM_WC + (T >> 2) * 2048 + ((q >> 1) * 8 + pp) * 128 + ((((q & 1) ^ pp) << 4) ^ ((2 * T & 7) << 4)));
            }
            const uint32_t oi = own ? ident : 0u;
            const uint32_t ra = sb + SM_W4 + (gc * 8 + pp) * 256;
#pragma unroll
            for (int u = 0; u < 4; ++u) {
                const uint32_t o = (u >> 1) * 128 + (((4 * (u & 1) + q) ^ ((pp + n0) & 7)) << 4);
                uint32_t r[4];
                ldsm4t(r, ra + o);
                at[2 * u][0] = r[0]; at[2 * u][1] = r[1]; at[2 * u + 1][0] = r[2]; at[2 * u + 1][1] = r[3];
                ldsm4t(r, ra + 32768 + o);
                mma16z(agg[2 * u], r[0], r[1], r[0], r[1], oi, oi);
                mma16z(agg[2 * u + 1], r[2], r[3], r[2], r[3], oi, oi);
            }
        }
        const uint32_t nlb = gc * 8 + 2 * t;
        do {
            if (slow && ks >= 0) {
                int n = 0;
                cp_wait<0>();
#pragma unroll 1
                while (scan_pos < kE && n <= kGCap - 32) {
                    const int e = scan_pos + lane;
                    const int d = e < kE ? __ldg(p.dst + e) - nb : -1;
                    const bool m = d >= lo && d < hi && (d >> 3) == warp;
                    const unsigned bal = __ballot_sync(0xffffffffu, m);
                    if (m) sts64(lbase + (warp * kGCap + n + __popc(bal & ((1u << lane) - 1))) * 8, (uint32_t)__ldg(p.src + e) | ((uint32_t)d << 25), (uint32_t)e * 32);
                    n += __popc(bal);
                    scan_pos += 32;
                }
                __syncwarp();
                nsteps = ke = max(1, (n + 7) >> 3);
                stab = ((warp * kGCap + lane * 8) & 0xFFF) | ((warp * kGCap + n) << 12) | (warp << 24);
                k = -1;
            }
#pragma unroll 1
            for (; k < ke; ++k) {
                uint32_t st_n = 0;
                if (k + 1 < nsteps) {
                    st_n = __shfl_sync(0xffffffffu, stab, k + 1);
                    const int idx_n = st_n & 0xFFF, end_n = (st_n >> 12) & 0xFFF;
                    const uint32_t slot = ring + ((k + 1) & 1) * kRingSlot;
                    const bool va = idx_n + q < end_n, vb = idx_n + 4 + q < end_n, vy = idx_n + g < end_n;
                    uint32_t wa = 0, wb = 0, wy = 0, cb = 0;
                    if (va) wa = lds32(lbase + (idx_n + q) * 8);
                    if (vb) wb = lds32(lbase + (idx_n + 4 + q) * 8);
                    if (vy) {
                        wy = lds32(lbase + (idx_n + g) * 8);
                        cb = lds32(lbase + (idx_n + g) * 8 + 4);
                    }
                    const unsigned char* pa = p.tab + (((wa & 0x3FFFu) << 8) | (((wa << 4) & 0x70u) ^ xa));
                    const unsigned char* pb = p.tab + (((wb & 0x3FFFu) << 8) | (((wb << 4) & 0x70u) ^ xa ^ 64u));
                    const uint32_t d = slot + lane * 16, na = va ? 16 : 0, nb2 = vb ? 16 : 0;
                    cp16z(d, pa, na);
                    cp16z(d + 2048, pa + kTab, na);
                    cp16z(d + 512, pb, nb2);
                    cp16z(d + 2560, pb + kTab, nb2);
                    cp16z(d + 1024, pa + 128, na);
                    cp16z(d + 3072, pa + kTab + 128, na);
                    cp16z(d + 1536, pb + 128, nb2);
                    cp16z(d + 3584, pb + kTab + 128, nb2);
                    cp8z(slot + 4096 + lane * 8, ea_base + cb + ((wy >> 9) & 0xFFE0u), vy ? 8 : 0);
                }
                cp_commit();
                if (k >= 0) {
                    const uint32_t slot = ring + (k & 1) * kRingSlot;
                    uint32_t wy = kPadRec;
                    if ((st_c & 0xFFF) + g < ((st_c >> 12) & 0xFFF)) wy = lds32(lbase + ((st_c & 0xFFF) + g) * 8);
                    cp_wait<1>();
                    __syncwarp();
                    uint32_t ea0, ea1;
                    asm volatile("ldmatrix.sync.aligned.m8n8.x2.shared.b16 {%0,%1}, [%2];" : "=r"(ea0), "=r"(ea1) : "r"(slot + 4096 + pp * 32 + (q & 1) * 16) : "memory");
                    ea0 = hfma2(ea0, 0x3F003F00u, 0x80008000u);
                    ea1 = hfma2(ea1, 0x3F003F00u, 0x80008000u);
                    const uint32_t dd = (wy >> 25) - nlb;
                    const uint32_t sT = dd == 0 ? 0x00003F00u : (dd == 1 ? 0x3F000000u : 0u);
                    const uint32_t sA = movm_t(sT);
#pragma unroll
                    for (int u = 0; u < 4; ++u) {
                        uint32_t bq[4], vq[4];
                        const uint32_t la = slot + ((u & 1) ? (lrd ^ 64u) : lrd) + (u >> 1) * 1024;
                        ldsm4(bq, la);
                        ldsm4t(vq, la + 2048);
#pragma unroll
                        for (int s = 0; s < 2; ++s) {
                            const int T = 2 * u + s;
                            float z[4];
                            mma16z(z, wc[T][0], wc[T][1], wc[T][2], wc[T][3], ea0, ea1);
                            mma8(z, at[T][0], at[T][1], sT);
                            mma16(z, ident, 0u, 0u, ident, bq[2 * s], bq[2 * s + 1]);
                            const uint32_t t01 = pack_bf16(tanh_fast(z[0]), tanh_fast(z[1]));
                            const uint32_t t23 = pack_bf16(tanh_fast(z[2]), tanh_fast(z[3]));
                            mma8(agg[T], hfma2(vq[2 * s], t01, vq[2 * s]), hfma2(vq[2 * s + 1], t23, vq[2 * s + 1]), sA);
                        }
                    }
                    __syncwarp();
                }
                st_c = st_n;
            }
        } while (slow && ks >= 0 && scan_pos < kE);
        if (ks < 0) {
            ks = 0;
            continue;
        }
        if (!own) {
            const uint32_t ex = exp_slot(sb, warp) + lane * 16;
#pragma unroll
            for (int T = 0; T < 8; ++T)
                sts128(ex + T * 512, __float_as_uint(agg[T][0]), __float_as_uint(agg[T][1]), __float_as_uint(agg[T][2]),
                       __float_as_uint(agg[T][3]));
            __syncwarp();
            if (lane == 0) mbar_arrive(sb + SM_MBAR + 40 + warp * 8);
        } else {
#pragma unroll 1
            for (unsigned m = imp; m; m &= m - 1) {
                const int w2 = __ffs(m) - 1;
                const uint32_t ex = exp_slot(sb, w2) + lane * 16;
                mbar_wait(sb + SM_MBAR + 40 + w2 * 8, 0);
#pragma unroll
                for (int T = 0; T < 8; ++T) {
                    const uint4 v = lds128(ex + T * 512);
                    agg[T][0] += __uint_as_float(v.x);
                    agg[T][1] += __uint_as_float(v.y);
                    agg[T][2] += __uint_as_float(v.z);
                    agg[T][3] += __uint_as_float(v.w);
                }
            }
            const uint32_t st = sb + SM_W4 + gc * 2048;
            __syncwarp();
#pragma unroll
            for (int u = 0; u < 4; ++u) {
                uint32_t pk[4];
#pragma unroll
                for (int j = 0; j < 4; ++j) {
                    const float h0 = 0.5f * agg[2 * u + (j >> 1)][2 * (j & 1)], h1 = 0.5f * agg[2 * u + (j >> 1)][2 * (j & 1) + 1];
                    pk[j] = pack_bf16(fmaf(h0, tanh_fast(h0), h0), fmaf(h1, tanh_fast(h1), h1));
                }
                stsm4t(st + pp * 256 + (u >> 1) * 128 + (((4 * (u & 1) + q) ^ pp) << 4), pk[0], pk[1], pk[2], pk[3]);
            }
            __syncwarp();
            {
                const int c = lane & 15, r0 = lane >> 4;
                unsigned char* o = p.out + (size_t)(nb + gc * 8 + r0) * 256 + c * 16;
                uint4 v[4];
#pragma unroll
                for (int i = 0; i < 4; ++i) v[i] = lds128(st + (r0 + 2 * i) * 256 + (c >> 3) * 128 + (((c & 7) ^ (r0 + 2 * i)) << 4));
#pragma unroll
                for (int i = 0; i < 4; ++i) {
                    const int nl = gc * 8 + r0 + 2 * i;
                    if (nl >= lo && nl < hi) *reinterpret_cast<uint4*>(o + i * 512) = v[i];
                }
            }
        }
        ks = slow ? nsteps : ke;
    }
    if (warp == 0) PROF(11);
}

}

typedef CUresult (*EncodeTiledFn)(CUtensorMap*, CUtensorMapDataType, cuuint32_t, void*, const cuuint64_t*, const cuuint64_t*,
                                  const cuuint32_t*, const cuuint32_t*, CUtensorMapInterleave, CUtensorMapSwizzle,
                                  CUtensorMapL2promotion, CUtensorMapFloatOOBfill);

static void encode_map(EncodeTiledFn enc, CUtensorMap* m, const void* base, int rows, int box_rows) {
    const cuuint64_t dims[2] = {128, (cuuint64_t)rows};
    const cuuint64_t strides[1] = {256};
    const cuuint32_t box[2] = {64, (cuuint32_t)box_rows};
    const cuuint32_t estr[2] = {1, 1};
    enc(m, CU_TENSOR_MAP_DATA_TYPE_BFLOAT16, 2, const_cast<void*>(base), dims, strides, box, estr, CU_TENSOR_MAP_INTERLEAVE_NONE,
        CU_TENSOR_MAP_SWIZZLE_128B, CU_TENSOR_MAP_L2_PROMOTION_L2_256B, CU_TENSOR_MAP_FLOAT_OOB_FILL_NONE);
}

extern "C" void kernel_launch(void* const* d_in, const int* in_sizes, int n_in, void* d_out, int out_size) {
    (void)in_sizes; (void)n_in; (void)out_size;
    static EncodeTiledFn enc = nullptr;
    if (!enc) {
        cudaFuncSetAttribute(egc::egc_kernel, cudaFuncAttributeMaxDynamicSharedMemorySize, egc::SM_TOTAL);
        void* fn = nullptr;
        cudaDriverEntryPointQueryResult qr;
        cudaGetDriverEntryPoint("cuTensorMapEncodeTiled", &fn, cudaEnableDefault, &qr);
        enc = (EncodeTiledFn)fn;
    }
    static void *slots_addr = nullptr, *tab_addr = nullptr, *bar_addr = nullptr;
    if (!slots_addr) {
        cudaGetSymbolAddress(&slots_addr, egc::g_slots);
        cudaGetSymbolAddress(&tab_addr, egc::g_T);
        cudaGetSymbolAddress(&bar_addr, egc::g_bar);
    }
    egc::Params p;
    p.tab = (unsigned char*)tab_addr;
    p.slots = (uint32_t*)slots_addr;
    p.bar = (unsigned*)bar_addr;
    {
        const cuuint64_t dims[2] = {egc::kG * egc::kSlot, egc::kG};
        const cuuint64_t strides[1] = {egc::kG * egc::kSlot * 4};
        const cuuint32_t box[2] = {egc::kSlot, egc::kG};
        const cuuint32_t estr[2] = {1, 1};
        enc(&p.ms, CU_TENSOR_MAP_DATA_TYPE_UINT32, 2, slots_addr, dims, strides, box, estr, CU_TENSOR_MAP_INTERLEAVE_NONE,
            CU_TENSOR_MAP_SWIZZLE_NONE, CU_TENSOR_MAP_L2_PROMOTION_NONE, CU_TENSOR_MAP_FLOAT_OOB_FILL_NONE);
    }
    encode_map(enc, &p.mx, d_in[0], egc::kN, egc::kRows);
    encode_map(enc, &p.mg, d_in[6], 272, 128);
    encode_map(enc, &p.mc, d_in[6], 272, 16);
    encode_map(enc, &p.mv, d_in[5], 128, 128);
    encode_map(enc, &p.mu, d_in[4], 128, 128);
    p.ea = (const unsigned char*)d_in[1];
    p.src = (const int*)d_in[2];
    p.dst = (const int*)d_in[3];
    p.out = (unsigned char*)d_out;
    egc::egc_kernel<<<egc::kG, egc::kThreads, egc::SM_TOTAL, cudaStreamPerThread>>>(p);
}
```

```cpp
#include <cuda_runtime.h>
#include <cuda.h>
#include <cuda_bf16.h>
#include <stdint.h>

namespace egc {

constexpr int kN = 10000;
constexpr int kE = 160000;
constexpr int kG = 132;
constexpr int kEPB = 1216;
constexpr int kWarps = 12;
constexpr int kThreads = kWarps * 32;
constexpr int kSlot = 32;
constexpr int kRows = 80;
constexpr int kNGrp = 10;
constexpr int kGCap = 192;
constexpr uint32_t kTab = kN * 256;
constexpr uint32_t kSentinel = 0xFFFFFFFFu;
constexpr uint32_t kOverflow = 126u << 25;
constexpr uint32_t kPadX = 1u, kPadY = 127u << 24;
constexpr int kSpinLimit = 1 << 22;
constexpr int kRingSlot = 4352;

static_assert(kN % 8 == 0 && kN < 16382, "src must fit 14 bits");
static_assert(kEPB * kG >= kE && kEPB <= 2048 && kEPB % 4 == 0 && kE % 4 == 0, "edge chunks");
static_assert(kG % kWarps == 0, "slot lines per warp");

constexpr int SM_X = 0;
constexpr int SM_W0 = 22528;
constexpr int SM_SLOT = SM_W0 + 4 * 16384;
constexpr int SM_RING = 0;
constexpr int SM_W4 = 105472;
constexpr int SM_WC = SM_W4 + 4 * 16384;
constexpr int SM_LIST = SM_WC + 4096;
constexpr int SM_EXP = SM_LIST + kNGrp * kGCap * 8;
constexpr int SM_NCNT = SM_EXP + 7 * 4096;
constexpr int SM_SCNT = SM_NCNT + 192;
constexpr int SM_MBAR = SM_SCNT + 544;
constexpr int SM_TOTAL = SM_MBAR + 17 * 8;
static_assert(SM_SLOT + kG * 128 <= SM_W4 && kWarps * 2 * kRingSlot <= SM_W4, "smem map");
static_assert(SM_W0 % 1024 == 0 && SM_W4 % 1024 == 0 && SM_WC % 1024 == 0 && SM_TOTAL <= 232448, "smem map");

__device__ __align__(1024) unsigned char g_T[2 * kTab];
__device__ __align__(1024) uint32_t g_slots[kG * kG * kSlot];
__device__ unsigned g_bar[64];

__device__ __forceinline__ uint32_t smem_u32(const void* p) { return (uint32_t)__cvta_generic_to_shared(p); }
__device__ __forceinline__ void cp16z(uint32_t dst, const void* src, uint32_t nbytes) {
    asm volatile("cp.async.cg.shared.global [%0], [%1], 16, %2;" ::"r"(dst), "l"(src), "r"(nbytes) : "memory");
}
__device__ __forceinline__ void cp8z(uint32_t dst, const void* src, uint32_t nbytes) {
    asm volatile("cp.async.ca.shared.global [%0], [%1], 8, %2;" ::"r"(dst), "l"(src), "r"(nbytes) : "memory");
}
__device__ __forceinline__ void named_arrive(int id, int n) { asm volatile("bar.arrive %0, %1;" ::"r"(id), "r"(n) : "memory"); }
__device__ __forceinline__ void named_wait(int id, int n) { asm volatile("bar.sync %0, %1;" ::"r"(id), "r"(n) : "memory"); }
__device__ __forceinline__ void grid_arrive(unsigned* ctr) {
    asm volatile("red.relaxed.gpu.global.add.u32 [%0], 1;" ::"l"(ctr) : "memory");
}
__device__ __forceinline__ void grid_wait(const unsigned* ctr, unsigned target) {
    unsigned v = 0;
    for (int it = 0; it < kSpinLimit; ++it) {
        asm volatile("ld.relaxed.gpu.global.u32 %0, [%1];" : "=r"(v) : "l"(ctr) : "memory");
        if ((int)(v - target) >= 0) break;
    }
}
__device__ __forceinline__ void cp_commit() { asm volatile("cp.async.commit_group;" ::: "memory"); }
template <int NPEND> __device__ __forceinline__ void cp_wait() { asm volatile("cp.async.wait_group %0;" ::"n"(NPEND) : "memory"); }
__device__ __forceinline__ void fence_async_smem() { asm volatile("fence.proxy.async.shared::cta;" ::: "memory"); }
template <int ID, int N> __device__ __forceinline__ void named_sync() { asm volatile("bar.sync %0, %1;" ::"n"(ID), "n"(N) : "memory"); }
__device__ __forceinline__ void bulk_store(void* gdst, uint32_t ssrc, uint32_t bytes) {
    asm volatile("cp.async.bulk.global.shared::cta.bulk_group [%0], [%1], %2;" ::"l"(gdst), "r"(ssrc), "r"(bytes) : "memory");
}
__device__ __forceinline__ void bulk_commit() { asm volatile("cp.async.bulk.commit_group;" ::: "memory"); }
__device__ __forceinline__ void mbar_init(uint32_t bar, uint32_t cnt) {
    asm volatile("mbarrier.init.shared::cta.b64 [%0], %1;" ::"r"(bar), "r"(cnt) : "memory");
}
__device__ __forceinline__ void mbar_expect(uint32_t bar, uint32_t bytes) {
    asm volatile("mbarrier.arrive.expect_tx.shared::cta.b64 _, [%0], %1;" ::"r"(bar), "r"(bytes) : "memory");
}
__device__ __forceinline__ void tma_load(uint32_t dst, const CUtensorMap* map, int col, int row, uint32_t bar) {
    asm volatile("cp.async.bulk.tensor.2d.shared::cluster.global.mbarrier::complete_tx::bytes [%0], [%1, {%3, %4}], [%2];"
                 ::"r"(dst), "l"(map), "r"(bar), "r"(col), "r"(row) : "memory");
}
__device__ __forceinline__ void mbar_arrive(uint32_t bar) {
    asm volatile("mbarrier.arrive.shared::cta.b64 _, [%0];" ::"r"(bar) : "memory");
}
__device__ __forceinline__ void mbar_wait(uint32_t bar, uint32_t parity) {
    asm volatile(
        "{\n"
        ".reg .pred p, q;\n"
        ".reg .u32 n;\n"
        "mov.u32 n, %2;\n"
        "WAIT_LOOP:\n"
        "mbarrier.try_wait.parity.shared::cta.b64 p, [%0], %1;\n"
        "sub.u32 n, n, 1;\n"
        "setp.ne.and.u32 q, n, 0, !p;\n"
        "@q bra WAIT_LOOP;\n"
        "}\n" ::"r"(bar), "r"(parity), "n"(kSpinLimit) : "memory");
}
__device__ __forceinline__ uint32_t lds32(uint32_t a) {
    uint32_t v;
    asm volatile("ld.shared.u32 %0, [%1];" : "=r"(v) : "r"(a) : "memory");
    return v;
}
__device__ __forceinline__ uint4 lds128(uint32_t a) {
    uint4 v;
    asm volatile("ld.shared.v4.u32 {%0,%1,%2,%3}, [%4];" : "=r"(v.x), "=r"(v.y), "=r"(v.z), "=r"(v.w) : "r"(a) : "memory");
    return v;
}
__device__ __forceinline__ void sts32(uint32_t a, uint32_t v) { asm volatile("st.shared.u32 [%0], %1;" ::"r"(a), "r"(v) : "memory"); }
__device__ __forceinline__ void sts64(uint32_t a, uint32_t x, uint32_t y) {
    asm volatile("st.shared.v2.u32 [%0], {%1,%2};" ::"r"(a), "r"(x), "r"(y) : "memory");
}
__device__ __forceinline__ void sts128(uint32_t a, uint32_t x, uint32_t y, uint32_t z, uint32_t w) {
    asm volatile("st.shared.v4.u32 [%0], {%1,%2,%3,%4};" ::"r"(a), "r"(x), "r"(y), "r"(z), "r"(w) : "memory");
}
__device__ __forceinline__ uint32_t atoms_inc(uint32_t a) {
    uint32_t old;
    asm volatile("atom.shared.add.u32 %0, [%1], 1;" : "=r"(old) : "r"(a) : "memory");
    return old;
}

__device__ __forceinline__ void ldsm4(uint32_t (&r)[4], uint32_t a) {
    asm volatile("ldmatrix.sync.aligned.m8n8.x4.shared.b16 {%0,%1,%2,%3}, [%4];"
                 : "=r"(r[0]), "=r"(r[1]), "=r"(r[2]), "=r"(r[3]) : "r"(a) : "memory");
}
__device__ __forceinline__ void ldsm4t(uint32_t (&r)[4], uint32_t a) {
    asm volatile("ldmatrix.sync.aligned.m8n8.x4.trans.shared.b16 {%0,%1,%2,%3}, [%4];"
                 : "=r"(r[0]), "=r"(r[1]), "=r"(r[2]), "=r"(r[3]) : "r"(a) : "memory");
}
__device__ __forceinline__ void stsm4t(uint32_t a, uint32_t r0, uint32_t r1, uint32_t r2, uint32_t r3) {
    asm volatile("stmatrix.sync.aligned.m8n8.x4.trans.shared.b16 [%0], {%1,%2,%3,%4};" ::"r"(a), "r"(r0), "r"(r1), "r"(r2), "r"(r3) : "memory");
}
__device__ __forceinline__ uint32_t pack_bf16(float lo, float hi) {
    uint32_t r;
    asm("cvt.rn.bf16x2.f32 %0, %1, %2;" : "=r"(r) : "f"(hi), "f"(lo));
    return r;
}
__device__ __forceinline__ uint32_t hfma2(uint32_t a, uint32_t b, uint32_t c) {
    uint32_t d;
    asm("fma.rn.bf16x2 %0, %1, %2, %3;" : "=r"(d) : "r"(a), "r"(b), "r"(c));
    return d;
}
__device__ __forceinline__ float tanh_fast(float x) {
    float r;
    asm("tanh.approx.f32 %0, %1;" : "=f"(r) : "f"(x));
    return r;
}
__device__ __forceinline__ void mma16z(float* d, uint32_t a0, uint32_t a1, uint32_t a2, uint32_t a3, uint32_t b0, uint32_t b1) {
    asm("mma.sync.aligned.m16n8k16.row.col.f32.bf16.bf16.f32 {%0,%1,%2,%3}, {%4,%5,%6,%7}, {%8,%9}, {%10,%10,%10,%10};"
        : "=f"(d[0]), "=f"(d[1]), "=f"(d[2]), "=f"(d[3])
        : "r"(a0), "r"(a1), "r"(a2), "r"(a3), "r"(b0), "r"(b1), "f"(0.f));
}
__device__ __forceinline__ void mma16(float* d, uint32_t a0, uint32_t a1, uint32_t a2, uint32_t a3, uint32_t b0, uint32_t b1) {
    asm("mma.sync.aligned.m16n8k16.row.col.f32.bf16.bf16.f32 {%0,%1,%2,%3}, {%4,%5,%6,%7}, {%8,%9}, {%0,%1,%2,%3};"
        : "+f"(d[0]), "+f"(d[1]), "+f"(d[2]), "+f"(d[3])
        : "r"(a0), "r"(a1), "r"(a2), "r"(a3), "r"(b0), "r"(b1));
}
__device__ __forceinline__ void mma8(float* d, uint32_t a0, uint32_t a1, uint32_t b0) {
    asm("mma.sync.aligned.m16n8k8.row.col.f32.bf16.bf16.f32 {%0,%1,%2,%3}, {%4,%5}, {%6}, {%0,%1,%2,%3};"
        : "+f"(d[0]), "+f"(d[1]), "+f"(d[2]), "+f"(d[3])
        : "r"(a0), "r"(a1), "r"(b0));
}
__device__ __forceinline__ uint32_t movm_t(uint32_t a) {
    uint32_t d;
    asm("movmatrix.sync.aligned.m8n8.trans.b16 %0, %1;" : "=r"(d) : "r"(a));
    return d;
}

__device__ __forceinline__ uint64_t make_desc(uint32_t lo) {
    uint64_t d;
    asm("mov.b64 %0, {%1, %2};" : "=l"(d) : "r"(lo), "r"(0x40000040u));
    return d;
}
__device__ __forceinline__ void wgmma_m64n80k16(float (&d)[40], uint64_t da, uint64_t db, int scale_d) {
    asm volatile(
        "{.reg .pred p; setp.ne.b32 p, %42, 0;\n"
        "wgmma.mma_async.sync.aligned.m64n80k16.f32.bf16.bf16 "
        "{%0,%1,%2,%3,%4,%5,%6,%7,%8,%9,%10,%11,%12,%13,%14,%15,%16,%17,%18,%19,"
        "%20,%21,%22,%23,%24,%25,%26,%27,%28,%29,%30,%31,%32,%33,%34,%35,%36,%37,%38,%39},"
        " %40, %41, p, 1, 1, 1, 0;}\n"
        : "+f"(d[0]), "+f"(d[1]), "+f"(d[2]), "+f"(d[3]), "+f"(d[4]), "+f"(d[5]), "+f"(d[6]), "+f"(d[7]),
          "+f"(d[8]), "+f"(d[9]), "+f"(d[10]), "+f"(d[11]), "+f"(d[12]), "+f"(d[13]), "+f"(d[14]), "+f"(d[15]),
          "+f"(d[16]), "+f"(d[17]), "+f"(d[18]), "+f"(d[19]), "+f"(d[20]), "+f"(d[21]), "+f"(d[22]), "+f"(d[23]),
          "+f"(d[24]), "+f"(d[25]), "+f"(d[26]), "+f"(d[27]), "+f"(d[28]), "+f"(d[29]), "+f"(d[30]), "+f"(d[31]),
          "+f"(d[32]), "+f"(d[33]), "+f"(d[34]), "+f"(d[35]), "+f"(d[36]), "+f"(d[37]), "+f"(d[38]), "+f"(d[39])
        : "l"(da), "l"(db), "r"(scale_d));
}

__device__ __forceinline__ int node_start(int b) { return (b * kN) / kG; }
__device__ __forceinline__ uint32_t exp_slot(uint32_t sb, int w) {
    return w <= 4 ? sb + SM_W4 + 22528 + ((w - 1) >> 1) * 32768 + ((w - 1) & 1) * 4096 : sb + SM_EXP + (w - 5) * 4096;
}

struct Params {
    const unsigned char* ea;
    const int* src;
    const int* dst;
    unsigned char* out;
    unsigned char* tab;
    uint32_t* slots;
    unsigned* bar;
    CUtensorMap mx;
    CUtensorMap mg;
    CUtensorMap mc;
    CUtensorMap mv;
    CUtensorMap mu;
    CUtensorMap ms;
};

__global__ void __launch_bounds__(kThreads, 1) egc_kernel(const __grid_constant__ Params p) {
    extern __shared__ __align__(1024) unsigned char smem[];
    const uint32_t sb = smem_u32(smem);
    const int tid = threadIdx.x, warp = tid >> 5, lane = tid & 31;
    const int b = blockIdx.x;
    const int n0 = node_start(b), n1 = node_start(b + 1);
    const int nb = n0;

    const int e0 = b * kEPB;
    const int nq = (min(kEPB, kE - e0)) >> 2;
    int4 d4, s4;
    if (tid < nq) {
        d4 = __ldg(reinterpret_cast<const int4*>(p.dst + e0) + tid);
        s4 = __ldg(reinterpret_cast<const int4*>(p.src + e0) + tid);
    }
    unsigned target = 0;
    if (tid == 288 || tid == 256) {
        asm volatile("ld.relaxed.gpu.global.u32 %0, [%1];" : "=r"(target) : "l"(p.bar + (tid == 256 ? 32 : 0)) : "memory");
        target = (target / kG + 1) * kG;
    }
    if (warp == 11) {
        if (lane < 6) asm volatile("prefetch.tensormap [%0];" ::"l"(&p.mx + lane) : "memory");
        if (lane == 0) {
#pragma unroll
            for (int i = 0; i < 5; ++i) mbar_init(sb + SM_MBAR + i * 8, 1);
            asm volatile("fence.mbarrier_init.release.cluster;" ::: "memory");
        }
        __syncwarp();
        named_arrive(4, 384);
        if (lane == 0) {
            mbar_expect(sb + SM_MBAR, 20480 + 32768);
            tma_load(sb + SM_X, &p.mx, 0, nb, sb + SM_MBAR);
            tma_load(sb + SM_X + 10240, &p.mx, 64, nb, sb + SM_MBAR);
            tma_load(sb + SM_W0, &p.mg, 0, 128, sb + SM_MBAR);
            tma_load(sb + SM_W0 + 16384, &p.mg, 64, 128, sb + SM_MBAR);
            mbar_expect(sb + SM_MBAR + 8, 32768);
            tma_load(sb + SM_W0 + 32768, &p.mv, 0, 0, sb + SM_MBAR + 8);
            tma_load(sb + SM_W0 + 49152, &p.mv, 64, 0, sb + SM_MBAR + 8);
            mbar_expect(sb + SM_MBAR + 16, 32768 + 4096);
            mbar_expect(sb + SM_MBAR + 24, 32768);
        }
        __syncwarp();
    } else {
        if (tid < 16) sts32(sb + SM_NCNT + tid * 4, 0);
        else if (tid >= 320 && tid < 320 + kWarps) mbar_init(sb + SM_MBAR + 40 + (tid - 320) * 8, 32);
        else if (tid >= 128 && tid < 128 + kG) sts32(sb + SM_SCNT + (tid - 128) * 4, 0);
#pragma unroll 1
        for (int i = tid; i < kG * 8; i += 352) sts128(sb + SM_SLOT + i * 16, kSentinel, kSentinel, kSentinel, kSentinel);
        named_wait(4, 384);
    }
    if (tid < nq) {
        const int dd[4] = {d4.x, d4.y, d4.z, d4.w};
        const int ss[4] = {s4.x, s4.y, s4.z, s4.w};
        uint32_t db[4], rank[4];
#pragma unroll
        for (int u = 0; u < 4; ++u) {
            db[u] = ((dd[u] + 1) * kG - 1) / kN;
            rank[u] = atoms_inc(sb + SM_SCNT + db[u] * 4);
        }
#pragma unroll
        for (int u = 0; u < 4; ++u) {
            const uint32_t nl = dd[u] - node_start(db[u]);
            if (rank[u] < kSlot)
                sts32(sb + SM_SLOT + db[u] * 128 + rank[u] * 4, (uint32_t)ss[u] | ((uint32_t)(tid * 4 + u) << 14) | (nl << 25));
        }
    }
    if (warp < 10) named_sync<5, 320>();
    if (warp == 8) {
#pragma unroll 1
        for (int d = lane; d < kG; d += 32)
            if (lds32(sb + SM_SCNT + d * 4) > kSlot) sts32(sb + SM_SLOT + d * 128, kOverflow);
        __syncwarp();
        if (lane == 0) {
            fence_async_smem();
            bulk_store(p.slots + (size_t)b * kG * kSlot, sb + SM_SLOT, kG * 128);
            bulk_commit();
            asm volatile("cp.async.bulk.wait_group 0;" ::: "memory");
            grid_arrive(p.bar);
        }
    } else if (warp == 10) {
#pragma unroll 1
        for (int i = lane; i < kNGrp * kGCap / 2; i += 32) sts128(sb + SM_LIST + i * 16, kPadX, kPadY, kPadX, kPadY);
        named_arrive(12, 64);
    } else if (warp == 9) {
        named_wait(12, 64);
        if (lane == 0) {
            asm volatile("prefetch.tensormap [%0];" ::"l"(&p.ms) : "memory");
            grid_wait(p.bar, target);
            mbar_expect(sb + SM_MBAR + 32, kG * 128);
            tma_load(sb + SM_SLOT, &p.ms, b * kSlot, 0, sb + SM_MBAR + 32);
        }
    } else if (warp == 11) {
        mbar_wait(sb + SM_MBAR, 0);
        if (lane < 6) {
            const int h = lane & 1, m = lane >> 1;
            tma_load(sb + (m == 1 ? SM_WC + h * 2048 : SM_W4 + (m >> 1) * 32768 + h * 16384), m == 0 ? &p.mg : (m == 1 ? &p.mc : &p.mu),
                     h * 64, m == 1 ? 256 : 0, sb + SM_MBAR + (m == 2 ? 24 : 16));
        }
    }
    __syncwarp();
    const int q = lane >> 3, pp = lane & 7;
    if (warp < 8) {
        const int wg = warp >> 2, w4 = warp & 3;
        const uint32_t xlo = ((sb + SM_X) >> 4) | 0x10000u;
        const uint32_t sw = wg * 128 + (((2 * w4 + (q & 1)) ^ ((pp + n0) & 7)) << 4);
#pragma unroll 1
        for (int pair = 0; pair < 4; ++pair) {
            const uint32_t wpair = sb + (pair < 2 ? SM_W0 : SM_W4 - 65536) + pair * 32768;
            mbar_wait(sb + SM_MBAR + pair * 8, 0);
            float acc[40];
            const uint32_t alo = ((wpair + wg * 16384) >> 4) | 0x10000u;
            asm volatile("wgmma.fence.sync.aligned;" ::: "memory");
#pragma unroll
            for (int s = 0; s < 8; ++s)
                wgmma_m64n80k16(acc, make_desc(alo + s * 128), make_desc(xlo + (s >> 2) * 640 + (s & 3) * 2), s);
            asm volatile("wgmma.commit_group.sync.aligned;" ::: "memory");
            asm volatile("wgmma.wait_group.sync.aligned 0;" ::: "memory");
#pragma unroll
            for (int i = 0; i < 40; ++i) asm volatile("" : "+f"(acc[i])::"memory");
            named_sync<1, 256>();
            const uint32_t a0 = wpair + ((q >> 1) * 8 + pp) * 256 + sw;
#pragma unroll
            for (int i = 0; i < 10; i += 2)
                stsm4t(a0 + i * 2048, pack_bf16(acc[4 * i], acc[4 * i + 1]), pack_bf16(acc[4 * i + 2], acc[4 * i + 3]),
                       pack_bf16(acc[4 * i + 4], acc[4 * i + 5]), pack_bf16(acc[4 * i + 6], acc[4 * i + 7]));
            if (pair < 2) named_arrive(9 + pair, 288);
        }
    } else {
        if (warp == 8) {
#pragma unroll 1
            for (int pair = 0; pair < 2; ++pair) {
                named_wait(9 + pair, 288);
                if (lane == 0) {
                    fence_async_smem();
                    bulk_store(p.tab + (size_t)pair * kTab + (size_t)n0 * 256, sb + SM_W0 + pair * 32768 + (n0 - nb) * 256, (n1 - n0) * 256);
                    bulk_commit();
                }
            }
            if (lane == 0) {
                asm volatile("cp.async.bulk.wait_group 0;" ::: "memory");
                grid_arrive(p.bar + 32);
            }
            __syncwarp();
        } else if (warp == 10) {
            mbar_wait(sb + SM_MBAR + 8, 0);
#pragma unroll 1
            for (int i = lane; i < nq; i += 32) asm volatile("prefetch.global.L2 [%0];" ::"l"(p.ea + (size_t)e0 * 32 + i * 128) : "memory");
        }
    }
    {
        const uint32_t c0 = 2 * warp + (lane >> 4);
        uint32_t off = (lane & 15) * 4;
        bool more;
        mbar_wait(sb + SM_MBAR + 32, 0);
#pragma unroll 1
        do {
            uint32_t rec[6], rank[6];
#pragma unroll
            for (int i = 0; i < 6; ++i) rec[i] = c0 + 24 * i < kG ? lds32(sb + SM_SLOT + (c0 + 24 * i) * 128 + off) : kSentinel;
            bool last = false;
#pragma unroll
            for (int i = 0; i < 6; ++i) {
                const bool valid = (rec[i] & 0x3FFFu) < (uint32_t)kN;
                last |= valid;
                rank[i] = atoms_inc(sb + SM_NCNT + (valid ? (rec[i] >> 28) : 16 + lane) * 4);
            }
#pragma unroll
            for (int i = 0; i < 6; ++i) {
                if (rank[i] < (uint32_t)kGCap && (rec[i] >> 28) < (uint32_t)kNGrp)
                    sts64(sb + SM_LIST + ((rec[i] >> 28) * kGCap + rank[i]) * 8, ((rec[i] & 0x3FFFu) << 8) | ((rec[i] & 7u) << 4),
                          (c0 + 24 * i) * (kEPB * 32) + ((rec[i] >> 9) & 0xFFE0u) + ((rec[i] >> 1) & 0x7F000000u));
            }
            more = off < 64 && __any_sync(0xffffffffu, last && (lane & 15) == 15);
            off += 64;
        } while (more);
    }
    if (tid == 256) grid_wait(p.bar + 32, target);
    __syncwarp();
    __syncthreads();

    const int g = lane >> 2, t = lane & 3;
    const int lo = n0 - nb, hi = n1 - nb;
    uint32_t cnt = lane < 16 ? lds32(sb + SM_NCNT + lane * 4) : 0;
    const bool slow = __any_sync(0xffffffffu, lane < kNGrp ? cnt > (uint32_t)kGCap : cnt != 0);
    const int ns = (lane < kNGrp && lane * 8 < hi) ? max(1, (int)(cnt + 7) >> 3) : 0;
    int sinc = ns;
#pragma unroll
    for (int o = 1; o < 16; o <<= 1) {
        const int v = __shfl_up_sync(0xffffffffu, sinc, o);
        if (lane >= o) sinc += v;
    }
    const int S = __shfl_sync(0xffffffffu, sinc, 15);
    const int k0 = (S * warp) / kWarps, k1 = (S * (warp + 1)) / kWarps;
    int sgrp = 0;
#pragma unroll
    for (int i = 0; i < kNGrp; ++i) sgrp += __shfl_sync(0xffffffffu, sinc, i) <= k0 + lane;
    sgrp = min(sgrp, kNGrp - 1);
    const int gtab = sinc | (ns << 16);
    uint32_t stab;
    {
        const int gt = __shfl_sync(0xffffffffu, gtab, sgrp);
        const int first = sgrp * kGCap + (k0 + lane - ((gt & 0xFFFF) - (gt >> 16))) * 8;
        stab = (first & 0xFFF) | (sgrp << 24);
    }
    int nsteps = k1 - k0;

    const uint32_t ident = (g == 2 * t) ? 0x00003F00u : ((g == 2 * t + 1) ? 0x3F000000u : 0u);
    const uint32_t xa = (pp ^ q) << 4;
    const uint32_t lrd = pp * 128 + ((q ^ pp) << 4);
    const uint32_t ring = sb + SM_RING + warp * (2 * kRingSlot);
    const uint32_t lbase = sb + SM_LIST;
    const unsigned char* ea_base = p.ea + t * 8;
    uint32_t wc[8][4], at[8][2];
    float agg[8][4];
    int scan_pos = 0;
    if (slow) {
        nsteps = (warp < kNGrp && warp * 8 < hi) ? 1 : 0;
        stab = warp << 24;
    }
    int k = -1;
    uint32_t st_c = 0;
#pragma unroll 1
    for (int ks = -1; ks < nsteps;) {
        int gc = 0, ke = 0, gend = 0;
        bool own = false;
        unsigned imp = 0;
        if (ks >= 0) {
            gc = __shfl_sync(0xffffffffu, stab, ks) >> 24;
            ke = ks + __popc(__ballot_sync(0xffffffffu, (int)(stab >> 24) == gc && lane >= ks && lane < nsteps));
            const int gt = __shfl_sync(0xffffffffu, gtab, gc);
            gend = gt & 0xFFFF;
            own = slow || gend - (gt >> 16) >= k0;
            if (own && !slow)
                imp = __ballot_sync(0xffffffffu, lane > warp && lane < kWarps && (S * lane) / kWarps < gend &&
                                                     (S * (lane + 1)) / kWarps != (S * lane) / kWarps);
            if (ks == 0) {
                mbar_wait(sb + SM_MBAR + 16, 0);
#pragma unroll
                for (int T = 0; T < 8; ++T)
                    ldsm4t(wc[T], sb + SM_WC + (T >> 2) * 2048 + ((q >> 1) * 8 + pp) * 128 + ((((q & 1) ^ pp) << 4) ^ ((2 * T & 7) << 4)));
            }
            const uint32_t oi = own ? ident : 0u;
            const uint32_t ra = sb + SM_W4 + (gc * 8 + pp) * 256;
#pragma unroll
            for (int u = 0; u < 4; ++u) {
                const uint32_t o = (u >> 1) * 128 + (((4 * (u & 1) + q) ^ ((pp + n0) & 7)) << 4);
                uint32_t r[4];
                ldsm4t(r, ra + o);
                at[2 * u][0] = r[0]; at[2 * u][1] = r[1]; at[2 * u + 1][0] = r[2]; at[2 * u + 1][1] = r[3];
                ldsm4t(r, ra + 32768 + o);
                mma16z(agg[2 * u], r[0], r[1], r[0], r[1], oi, oi);
                mma16z(agg[2 * u + 1], r[2], r[3], r[2], r[3], oi, oi);
            }
        }
        const uint32_t nlb = gc * 8 + 2 * t;
        do {
            if (slow && ks >= 0) {
                int n = 0;
                cp_wait<0>();
#pragma unroll 1
                while (scan_pos < kE && n <= kGCap - 32) {
                    const int e = scan_pos + lane;
                    const int d = e < kE ? __ldg(p.dst + e) - nb : -1;
                    const bool m = d >= lo && d < hi && (d >> 3) == warp;
                    const unsigned bal = __ballot_sync(0xffffffffu, m);
                    if (m) {
                        const uint32_t s = __ldg(p.src + e);
                        sts64(lbase + (warp * kGCap + n + __popc(bal & ((1u << lane) - 1))) * 8, (s << 8) | ((s & 7u) << 4), (uint32_t)e * 32 + ((uint32_t)d << 24));
                    }
                    n += __popc(bal);
                    scan_pos += 32;
                }
                if (lane < 8) sts64(lbase + (warp * kGCap + n + lane) * 8, kPadX, kPadY);
                __syncwarp();
                nsteps = ke = max(1, (n + 7) >> 3);
                stab = ((warp * kGCap + lane * 8) & 0xFFF) | (warp << 24);
                k = -1;
            }
#pragma unroll 1
            for (; k < ke; ++k) {
                uint32_t st_n = 0;
                if (k + 1 < nsteps) {
                    st_n = __shfl_sync(0xffffffffu, stab, k + 1);
                    const uint32_t la = lbase + (st_n & 0xFFF) * 8;
                    const uint32_t slot = ring + ((k + 1) & 1) * kRingSlot;
                    const uint32_t wa = lds32(la + q * 8), wb = lds32(la + q * 8 + 32), wy = lds32(la + g * 8 + 4);
                    const unsigned char* pa = p.tab + ((wa & 0xFFFFFFF0u) ^ xa);
                    const unsigned char* pb = p.tab + ((wb & 0xFFFFFFF0u) ^ xa ^ 64u);
                    const uint32_t d = slot + lane * 16, na = (wa & 1) ? 0 : 16, nb2 = (wb & 1) ? 0 : 16;
                    cp16z(d, pa, na);
                    cp16z(d + 2048, pa + kTab, na);
                    cp16z(d + 512, pb, nb2);
                    cp16z(d + 2560, pb + kTab, nb2);
                    cp16z(d + 1024, pa + 128, na);
                    cp16z(d + 3072, pa + kTab + 128, na);
                    cp16z(d + 1536, pb + 128, nb2);
                    cp16z(d + 3584, pb + kTab + 128, nb2);
                    cp8z(slot + 4096 + lane * 8, ea_base + (wy & 0xFFFFFFu), wy != kPadY ? 8 : 0);
                }
                cp_commit();
                if (k >= 0) {
                    const uint32_t slot = ring + (k & 1) * kRingSlot;
                    const uint32_t wy = lds32(lbase + ((st_c & 0xFFF) + g) * 8 + 4);
                    cp_wait<1>();
                    __syncwarp();
                    uint32_t ea0, ea1;
                    asm volatile("ldmatrix.sync.aligned.m8n8.x2.shared.b16 {%0,%1}, [%2];" : "=r"(ea0), "=r"(ea1) : "r"(slot + 4096 + pp * 32 + (q & 1) * 16) : "memory");
                    ea0 = hfma2(ea0, 0x3F003F00u, 0x80008000u);
                    ea1 = hfma2(ea1, 0x3F003F00u, 0x80008000u);
                    const uint32_t dd = (wy >> 24) - nlb;
                    const uint32_t sT = dd == 0 ? 0x00003F00u : (dd == 1 ? 0x3F000000u : 0u);
                    const uint32_t sA = movm_t(sT);
#pragma unroll
                    for (int u = 0; u < 4; ++u) {
                        uint32_t bq[4], vq[4];
                        const uint32_t la = slot + ((u & 1) ? (lrd ^ 64u) : lrd) + (u >> 1) * 1024;
                        ldsm4(bq, la);
                        ldsm4t(vq, la + 2048);
#pragma unroll
                        for (int s = 0; s < 2; ++s) {
                            const int T = 2 * u + s;
                            float z[4];
                            mma16z(z, wc[T][0], wc[T][1], wc[T][2], wc[T][3], ea0, ea1);
                            mma8(z, at[T][0], at[T][1], sT);
                            mma16(z, ident, 0u, 0u, ident, bq[2 * s], bq[2 * s + 1]);
                            const uint32_t t01 = pack_bf16(tanh_fast(z[0]), tanh_fast(z[1]));
                            const uint32_t t23 = pack_bf16(tanh_fast(z[2]), tanh_fast(z[3]));
                            mma8(agg[T], hfma2(vq[2 * s], t01, vq[2 * s]), hfma2(vq[2 * s + 1], t23, vq[2 * s + 1]), sA);
                        }
                    }
                    __syncwarp();
                }
                st_c = st_n;
            }
        } while (slow && ks >= 0 && scan_pos < kE);
        if (ks < 0) {
            ks = 0;
            continue;
        }
        if (!own) {
            const uint32_t ex = exp_slot(sb, warp) + lane * 16;
#pragma unroll
            for (int T = 0; T < 8; ++T)
                sts128(ex + T * 512, __float_as_uint(agg[T][0]), __float_as_uint(agg[T][1]), __float_as_uint(agg[T][2]),
                       __float_as_uint(agg[T][3]));
            mbar_arrive(sb + SM_MBAR + 40 + warp * 8);
        } else {
#pragma unroll 1
            for (unsigned m = imp; m; m &= m - 1) {
                const int w2 = __ffs(m) - 1;
                const uint32_t ex = exp_slot(sb, w2) + lane * 16;
                mbar_wait(sb + SM_MBAR + 40 + w2 * 8, 0);
#pragma unroll
                for (int T = 0; T < 8; ++T) {
                    const uint4 v = lds128(ex + T * 512);
                    agg[T][0] += __uint_as_float(v.x);
                    agg[T][1] += __uint_as_float(v.y);
                    agg[T][2] += __uint_as_float(v.z);
                    agg[T][3] += __uint_as_float(v.w);
                }
            }
            const uint32_t st = sb + SM_W4 + gc * 2048;
            __syncwarp();
#pragma unroll
            for (int u = 0; u < 4; ++u) {
                uint32_t pk[4];
#pragma unroll
                for (int j = 0; j < 4; ++j) {
                    const float h0 = 0.5f * agg[2 * u + (j >> 1)][2 * (j & 1)], h1 = 0.5f * agg[2 * u + (j >> 1)][2 * (j & 1) + 1];
                    pk[j] = pack_bf16(fmaf(h0, tanh_fast(h0), h0), fmaf(h1, tanh_fast(h1), h1));
                }
                stsm4t(st + pp * 256 + (u >> 1) * 128 + (((4 * (u & 1) + q) ^ pp) << 4), pk[0], pk[1], pk[2], pk[3]);
            }
            __syncwarp();
            {
                const int c = lane & 15, r0 = lane >> 4;
                unsigned char* o = p.out + (size_t)(nb + gc * 8 + r0) * 256 + c * 16;
                uint4 v[4];
#pragma unroll
                for (int i = 0; i < 4; ++i) v[i] = lds128(st + (r0 + 2 * i) * 256 + (c >> 3) * 128 + (((c & 7) ^ (r0 + 2 * i)) << 4));
#pragma unroll
                for (int i = 0; i < 4; ++i) {
                    const int nl = gc * 8 + r0 + 2 * i;
                    if (nl >= lo && nl < hi) *reinterpret_cast<uint4*>(o + i * 512) = v[i];
                }
            }
        }
        ks = slow ? nsteps : ke;
    }
}

}

typedef CUresult (*EncodeTiledFn)(CUtensorMap*, CUtensorMapDataType, cuuint32_t, void*, const cuuint64_t*, const cuuint64_t*,
                                  const cuuint32_t*, const cuuint32_t*, CUtensorMapInterleave, CUtensorMapSwizzle,
                                  CUtensorMapL2promotion, CUtensorMapFloatOOBfill);

static void encode_map(EncodeTiledFn enc, CUtensorMap* m, const void* base, int rows, int box_rows) {
    const cuuint64_t dims[2] = {128, (cuuint64_t)rows};
    const cuuint64_t strides[1] = {256};
    const cuuint32_t box[2] = {64, (cuuint32_t)box_rows};
    const cuuint32_t estr[2] = {1, 1};
    enc(m, CU_TENSOR_MAP_DATA_TYPE_BFLOAT16, 2, const_cast<void*>(base), dims, strides, box, estr, CU_TENSOR_MAP_INTERLEAVE_NONE,
        CU_TENSOR_MAP_SWIZZLE_128B, CU_TENSOR_MAP_L2_PROMOTION_L2_256B, CU_TENSOR_MAP_FLOAT_OOB_FILL_NONE);
}

extern "C" void kernel_launch(void* const* d_in, const int* in_sizes, int n_in, void* d_out, int out_size) {
    (void)in_sizes; (void)n_in; (void)out_size;
    static EncodeTiledFn enc = nullptr;
    if (!enc) {
        cudaFuncSetAttribute(egc::egc_kernel, cudaFuncAttributeMaxDynamicSharedMemorySize, egc::SM_TOTAL);
        void* fn = nullptr;
        cudaDriverEntryPointQueryResult qr;
        cudaGetDriverEntryPoint("cuTensorMapEncodeTiled", &fn, cudaEnableDefault, &qr);
        enc = (EncodeTiledFn)fn;
    }
    static void *slots_addr = nullptr, *tab_addr = nullptr, *bar_addr = nullptr;
    if (!slots_addr) {
        cudaGetSymbolAddress(&slots_addr, egc::g_slots);
        cudaGetSymbolAddress(&tab_addr, egc::g_T);
        cudaGetSymbolAddress(&bar_addr, egc::g_bar);
    }
    egc::Params p;
    p.tab = (unsigned char*)tab_addr;
    p.slots = (uint32_t*)slots_addr;
    p.bar = (unsigned*)bar_addr;
    {
        const cuuint64_t dims[2] = {egc::kG * egc::kSlot, egc::kG};
        const cuuint64_t strides[1] = {egc::kG * egc::kSlot * 4};
        const cuuint32_t box[2] = {egc::kSlot, egc::kG};
        const cuuint32_t estr[2] = {1, 1};
        enc(&p.ms, CU_TENSOR_MAP_DATA_TYPE_UINT32, 2, slots_addr, dims, strides, box, estr, CU_TENSOR_MAP_INTERLEAVE_NONE,
            CU_TENSOR_MAP_SWIZZLE_NONE, CU_TENSOR_MAP_L2_PROMOTION_NONE, CU_TENSOR_MAP_FLOAT_OOB_FILL_NONE);
    }
    encode_map(enc, &p.mx, d_in[0], egc::kN, egc::kRows);
    encode_map(enc, &p.mg, d_in[6], 272, 128);
    encode_map(enc, &p.mc, d_in[6], 272, 16);
    encode_map(enc, &p.mv, d_in[5], 128, 128);
    encode_map(enc, &p.mu, d_in[4], 128, 128);
    p.ea = (const unsigned char*)d_in[1];
    p.src = (const int*)d_in[2];
    p.dst = (const int*)d_in[3];
    p.out = (unsigned char*)d_out;
    egc::egc_kernel<<<egc::kG, egc::kThreads, egc::SM_TOTAL, cudaStreamPerThread>>>(p);
}
```

```cpp
#include <cuda_runtime.h>
#include <cuda.h>
#include <cuda_bf16.h>
#include <stdint.h>

namespace egc {

constexpr int kN = 10000;
constexpr int kE = 160000;
constexpr int kG = 132;
constexpr int kEPB = 1216;
constexpr int kWarps = 12;
constexpr int kThreads = kWarps * 32;
constexpr int kSlot = 32;
constexpr int kRows = 80;
constexpr int kNGrp = 10;
constexpr int kGCap = 192;
constexpr uint32_t kTab = kN * 256;
constexpr uint32_t kSentinel = 0xFFFFFFFFu;
constexpr uint32_t kOverflow = 126u << 25;
constexpr uint32_t kPadX = 1u, kPadY = 127u << 24;
constexpr int kSpinLimit = 1 << 22;
constexpr int kRingSlot = 4352;

static_assert(kN % 8 == 0 && kN < 16382, "src must fit 14 bits");
static_assert(kEPB * kG >= kE && kEPB <= 2048 && kEPB % 4 == 0 && kE % 4 == 0, "edge chunks");
static_assert(kG % kWarps == 0, "slot lines per warp");

constexpr int SM_X = 0;
constexpr int SM_W0 = 22528;
constexpr int SM_SLOT = SM_W0 + 4 * 16384;
constexpr int SM_RING = 0;
constexpr int SM_W4 = 105472;
constexpr int SM_WC = SM_W4 + 4 * 16384;
constexpr int SM_LIST = SM_WC + 4096;
constexpr int SM_EXP = SM_LIST + kNGrp * kGCap * 8;
constexpr int SM_NCNT = SM_EXP + 7 * 4096;
constexpr int SM_SCNT = SM_NCNT + 192;
constexpr int SM_MBAR = SM_SCNT + 544;
constexpr int SM_TOTAL = SM_MBAR + 17 * 8;
static_assert(SM_SLOT + kG * 128 <= SM_W4 && kWarps * 2 * kRingSlot <= SM_W4, "smem map");
static_assert(SM_W0 % 1024 == 0 && SM_W4 % 1024 == 0 && SM_WC % 1024 == 0 && SM_TOTAL <= 232448, "smem map");

__device__ __align__(1024) unsigned char g_T[2 * kTab];
__device__ __align__(1024) uint32_t g_slots[kG * kG * kSlot];
__device__ unsigned g_bar[64];

__device__ __forceinline__ uint32_t smem_u32(const void* p) { return (uint32_t)__cvta_generic_to_shared(p); }
__device__ __forceinline__ void cp16z(uint32_t dst, const void* src, uint32_t nbytes) {
    asm volatile("cp.async.cg.shared.global [%0], [%1], 16, %2;" ::"r"(dst), "l"(src), "r"(nbytes) : "memory");
}
__device__ __forceinline__ void cp8z(uint32_t dst, const void* src, uint32_t nbytes) {
    asm volatile("cp.async.ca.shared.global [%0], [%1], 8, %2;" ::"r"(dst), "l"(src), "r"(nbytes) : "memory");
}
__device__ __forceinline__ void named_arrive(int id, int n) { asm volatile("bar.arrive %0, %1;" ::"r"(id), "r"(n) : "memory"); }
__device__ __forceinline__ void named_wait(int id, int n) { asm volatile("bar.sync %0, %1;" ::"r"(id), "r"(n) : "memory"); }
__device__ __forceinline__ void grid_arrive(unsigned* ctr) {
    asm volatile("red.relaxed.gpu.global.add.u32 [%0], 1;" ::"l"(ctr) : "memory");
}
__device__ __forceinline__ void grid_wait(const unsigned* ctr, unsigned target) {
    unsigned v = 0;
    for (int it = 0; it < kSpinLimit; ++it) {
        asm volatile("ld.relaxed.gpu.global.u32 %0, [%1];" : "=r"(v) : "l"(ctr) : "memory");
        if ((int)(v - target) >= 0) break;
    }
}
__device__ __forceinline__ void cp_commit() { asm volatile("cp.async.commit_group;" ::: "memory"); }
template <int NPEND> __device__ __forceinline__ void cp_wait() { asm volatile("cp.async.wait_group %0;" ::"n"(NPEND) : "memory"); }
__device__ __forceinline__ void fence_async_smem() { asm volatile("fence.proxy.async.shared::cta;" ::: "memory"); }
template <int ID, int N> __device__ __forceinline__ void named_sync() { asm volatile("bar.sync %0, %1;" ::"n"(ID), "n"(N) : "memory"); }
__device__ __forceinline__ void bulk_store(void* gdst, uint32_t ssrc, uint32_t bytes) {
    asm volatile("cp.async.bulk.global.shared::cta.bulk_group [%0], [%1], %2;" ::"l"(gdst), "r"(ssrc), "r"(bytes) : "memory");
}
__device__ __forceinline__ void bulk_commit() { asm volatile("cp.async.bulk.commit_group;" ::: "memory"); }
__device__ __forceinline__ void mbar_init(uint32_t bar, uint32_t cnt) {
    asm volatile("mbarrier.init.shared::cta.b64 [%0], %1;" ::"r"(bar), "r"(cnt) : "memory");
}
__device__ __forceinline__ void mbar_expect(uint32_t bar, uint32_t bytes) {
    asm volatile("mbarrier.arrive.expect_tx.shared::cta.b64 _, [%0], %1;" ::"r"(bar), "r"(bytes) : "memory");
}
__device__ __forceinline__ void tma_load(uint32_t dst, const CUtensorMap* map, int col, int row, uint32_t bar) {
    asm volatile("cp.async.bulk.tensor.2d.shared::cluster.global.mbarrier::complete_tx::bytes [%0], [%1, {%3, %4}], [%2];"
                 ::"r"(dst), "l"(map), "r"(bar), "r"(col), "r"(row) : "memory");
}
__device__ __forceinline__ void mbar_arrive(uint32_t bar) {
    asm volatile("mbarrier.arrive.shared::cta.b64 _, [%0];" ::"r"(bar) : "memory");
}
__device__ __forceinline__ void mbar_wait(uint32_t bar, uint32_t parity) {
    asm volatile(
        "{\n"
        ".reg .pred p, q;\n"
        ".reg .u32 n;\n"
        "mov.u32 n, %2;\n"
        "WAIT_LOOP:\n"
        "mbarrier.try_wait.parity.shared::cta.b64 p, [%0], %1;\n"
        "sub.u32 n, n, 1;\n"
        "setp.ne.and.u32 q, n, 0, !p;\n"
        "@q bra WAIT_LOOP;\n"
        "}\n" ::"r"(bar), "r"(parity), "n"(kSpinLimit) : "memory");
}
__device__ __forceinline__ uint32_t lds32(uint32_t a) {
    uint32_t v;
    asm volatile("ld.shared.u32 %0, [%1];" : "=r"(v) : "r"(a) : "memory");
    return v;
}
__device__ __forceinline__ uint4 lds128(uint32_t a) {
    uint4 v;
    asm volatile("ld.shared.v4.u32 {%0,%1,%2,%3}, [%4];" : "=r"(v.x), "=r"(v.y), "=r"(v.z), "=r"(v.w) : "r"(a) : "memory");
    return v;
}
__device__ __forceinline__ void sts32(uint32_t a, uint32_t v) { asm volatile("st.shared.u32 [%0], %1;" ::"r"(a), "r"(v) : "memory"); }
__device__ __forceinline__ void sts64(uint32_t a, uint32_t x, uint32_t y) {
    asm volatile("st.shared.v2.u32 [%0], {%1,%2};" ::"r"(a), "r"(x), "r"(y) : "memory");
}
__device__ __forceinline__ void sts128(uint32_t a, uint32_t x, uint32_t y, uint32_t z, uint32_t w) {
    asm volatile("st.shared.v4.u32 [%0], {%1,%2,%3,%4};" ::"r"(a), "r"(x), "r"(y), "r"(z), "r"(w) : "memory");
}
__device__ __forceinline__ uint32_t atoms_inc(uint32_t a) {
    uint32_t old;
    asm volatile("atom.shared.add.u32 %0, [%1], 1;" : "=r"(old) : "r"(a) : "memory");
    return old;
}

__device__ __forceinline__ void ldsm4(uint32_t (&r)[4], uint32_t a) {
    asm volatile("ldmatrix.sync.aligned.m8n8.x4.shared.b16 {%0,%1,%2,%3}, [%4];"
                 : "=r"(r[0]), "=r"(r[1]), "=r"(r[2]), "=r"(r[3]) : "r"(a) : "memory");
}
__device__ __forceinline__ void ldsm4t(uint32_t (&r)[4], uint32_t a) {
    asm volatile("ldmatrix.sync.aligned.m8n8.x4.trans.shared.b16 {%0,%1,%2,%3}, [%4];"
                 : "=r"(r[0]), "=r"(r[1]), "=r"(r[2]), "=r"(r[3]) : "r"(a) : "memory");
}
__device__ __forceinline__ void stsm4t(uint32_t a, uint32_t r0, uint32_t r1, uint32_t r2, uint32_t r3) {
    asm volatile("stmatrix.sync.aligned.m8n8.x4.trans.shared.b16 [%0], {%1,%2,%3,%4};" ::"r"(a), "r"(r0), "r"(r1), "r"(r2), "r"(r3) : "memory");
}
__device__ __forceinline__ uint32_t pack_bf16(float lo, float hi) {
    uint32_t r;
    asm("cvt.rn.bf16x2.f32 %0, %1, %2;" : "=r"(r) : "f"(hi), "f"(lo));
    return r;
}
__device__ __forceinline__ uint32_t hfma2(uint32_t a, uint32_t b, uint32_t c) {
    uint32_t d;
    asm("fma.rn.bf16x2 %0, %1, %2, %3;" : "=r"(d) : "r"(a), "r"(b), "r"(c));
    return d;
}
__device__ __forceinline__ float tanh_fast(float x) {
    float r;
    asm("tanh.approx.f32 %0, %1;" : "=f"(r) : "f"(x));
    return r;
}
__device__ __forceinline__ void mma16z(float* d, uint32_t a0, uint32_t a1, uint32_t a2, uint32_t a3, uint32_t b0, uint32_t b1) {
    asm("mma.sync.aligned.m16n8k16.row.col.f32.bf16.bf16.f32 {%0,%1,%2,%3}, {%4,%5,%6,%7}, {%8,%9}, {%10,%10,%10,%10};"
        : "=f"(d[0]), "=f"(d[1]), "=f"(d[2]), "=f"(d[3])
        : "r"(a0), "r"(a1), "r"(a2), "r"(a3), "r"(b0), "r"(b1), "f"(0.f));
}
__device__ __forceinline__ void mma16(float* d, uint32_t a0, uint32_t a1, uint32_t a2, uint32_t a3, uint32_t b0, uint32_t b1) {
    asm("mma.sync.aligned.m16n8k16.row.col.f32.bf16.bf16.f32 {%0,%1,%2,%3}, {%4,%5,%6,%7}, {%8,%9}, {%0,%1,%2,%3};"
        : "+f"(d[0]), "+f"(d[1]), "+f"(d[2]), "+f"(d[3])
        : "r"(a0), "r"(a1), "r"(a2), "r"(a3), "r"(b0), "r"(b1));
}
__device__ __forceinline__ void mma8(float* d, uint32_t a0, uint32_t a1, uint32_t b0) {
    asm("mma.sync.aligned.m16n8k8.row.col.f32.bf16.bf16.f32 {%0,%1,%2,%3}, {%4,%5}, {%6}, {%0,%1,%2,%3};"
        : "+f"(d[0]), "+f"(d[1]), "+f"(d[2]), "+f"(d[3])
        : "r"(a0), "r"(a1), "r"(b0));
}
__device__ __forceinline__ uint32_t movm_t(uint32_t a) {
    uint32_t d;
    asm("movmatrix.sync.aligned.m8n8.trans.b16 %0, %1;" : "=r"(d) : "r"(a));
    return d;
}

__device__ __forceinline__ uint64_t make_desc(uint32_t lo) {
    uint64_t d;
    asm("mov.b64 %0, {%1, %2};" : "=l"(d) : "r"(lo), "r"(0x40000040u));
    return d;
}
__device__ __forceinline__ void wgmma_m64n80k16(float (&d)[40], uint64_t da, uint64_t db, int scale_d) {
    asm volatile(
        "{.reg .pred p; setp.ne.b32 p, %42, 0;\n"
        "wgmma.mma_async.sync.aligned.m64n80k16.f32.bf16.bf16 "
        "{%0,%1,%2,%3,%4,%5,%6,%7,%8,%9,%10,%11,%12,%13,%14,%15,%16,%17,%18,%19,"
        "%20,%21,%22,%23,%24,%25,%26,%27,%28,%29,%30,%31,%32,%33,%34,%35,%36,%37,%38,%39},"
        " %40, %41, p, 1, 1, 1, 0;}\n"
        : "+f"(d[0]), "+f"(d[1]), "+f"(d[2]), "+f"(d[3]), "+f"(d[4]), "+f"(d[5]), "+f"(d[6]), "+f"(d[7]),
          "+f"(d[8]), "+f"(d[9]), "+f"(d[10]), "+f"(d[11]), "+f"(d[12]), "+f"(d[13]), "+f"(d[14]), "+f"(d[15]),
          "+f"(d[16]), "+f"(d[17]), "+f"(d[18]), "+f"(d[19]), "+f"(d[20]), "+f"(d[21]), "+f"(d[22]), "+f"(d[23]),
          "+f"(d[24]), "+f"(d[25]), "+f"(d[26]), "+f"(d[27]), "+f"(d[28]), "+f"(d[29]), "+f"(d[30]), "+f"(d[31]),
          "+f"(d[32]), "+f"(d[33]), "+f"(d[34]), "+f"(d[35]), "+f"(d[36]), "+f"(d[37]), "+f"(d[38]), "+f"(d[39])
        : "l"(da), "l"(db), "r"(scale_d));
}

__device__ __forceinline__ int node_start(int b) { return (b * kN) / kG; }
__device__ __forceinline__ uint32_t exp_slot(uint32_t sb, int w) {
    return w <= 4 ? sb + SM_W4 + 22528 + ((w - 1) >> 1) * 32768 + ((w - 1) & 1) * 4096 : sb + SM_EXP + (w - 5) * 4096;
}

struct Params {
    const unsigned char* ea;
    const int* src;
    const int* dst;
    unsigned char* out;
    unsigned char* tab;
    uint32_t* slots;
    unsigned* bar;
    CUtensorMap mx;
    CUtensorMap mg;
    CUtensorMap mc;
    CUtensorMap mv;
    CUtensorMap mu;
    CUtensorMap ms;
};

__global__ void __launch_bounds__(kThreads, 1) egc_kernel(const __grid_constant__ Params p) {
    extern __shared__ __align__(1024) unsigned char smem[];
    const uint32_t sb = smem_u32(smem);
    const int tid = threadIdx.x, warp = tid >> 5, lane = tid & 31;
    const int b = blockIdx.x;
    const int n0 = node_start(b), n1 = node_start(b + 1);
    const int nb = n0;

    const int e0 = b * kEPB;
    const int nq = (min(kEPB, kE - e0)) >> 2;
    int4 d4, s4;
    if (tid < nq) {
        d4 = __ldg(reinterpret_cast<const int4*>(p.dst + e0) + tid);
        s4 = __ldg(reinterpret_cast<const int4*>(p.src + e0) + tid);
    }
    unsigned target = 0;
    if (tid == 288 || tid == 256) {
        asm volatile("ld.relaxed.gpu.global.u32 %0, [%1];" : "=r"(target) : "l"(p.bar + (tid == 256 ? 32 : 0)) : "memory");
        target = (target / kG + 1) * kG;
    }
    if (warp == 11) {
        if (lane < 6) asm volatile("prefetch.tensormap [%0];" ::"l"(&p.mx + lane) : "memory");
        if (lane == 0) {
#pragma unroll
            for (int i = 0; i < 5; ++i) mbar_init(sb + SM_MBAR + i * 8, 1);
            asm volatile("fence.mbarrier_init.release.cluster;" ::: "memory");
        }
        __syncwarp();
        named_arrive(4, 384);
        if (lane == 0) {
            mbar_expect(sb + SM_MBAR, 20480 + 32768);
            tma_load(sb + SM_X, &p.mx, 0, nb, sb + SM_MBAR);
            tma_load(sb + SM_X + 10240, &p.mx, 64, nb, sb + SM_MBAR);
            tma_load(sb + SM_W0, &p.mg, 0, 128, sb + SM_MBAR);
            tma_load(sb + SM_W0 + 16384, &p.mg, 64, 128, sb + SM_MBAR);
            mbar_expect(sb + SM_MBAR + 8, 32768);
            tma_load(sb + SM_W0 + 32768, &p.mv, 0, 0, sb + SM_MBAR + 8);
            tma_load(sb + SM_W0 + 49152, &p.mv, 64, 0, sb + SM_MBAR + 8);
            mbar_expect(sb + SM_MBAR + 16, 32768 + 4096);
            mbar_expect(sb + SM_MBAR + 24, 32768);
        }
        __syncwarp();
    } else {
        if (tid < 16) sts32(sb + SM_NCNT + tid * 4, 0);
        else if (tid >= 320 && tid < 320 + kWarps) mbar_init(sb + SM_MBAR + 40 + (tid - 320) * 8, 32);
        else if (tid >= 128 && tid < 128 + kG) sts32(sb + SM_SCNT + (tid - 128) * 4, 0);
#pragma unroll 1
        for (int i = tid; i < kG * 8; i += 352) sts128(sb + SM_SLOT + i * 16, kSentinel, kSentinel, kSentinel, kSentinel);
        named_wait(4, 384);
    }
    if (tid < nq) {
        const int dd[4] = {d4.x, d4.y, d4.z, d4.w};
        const int ss[4] = {s4.x, s4.y, s4.z, s4.w};
        uint32_t db[4], rank[4];
#pragma unroll
        for (int u = 0; u < 4; ++u) {
            db[u] = ((dd[u] + 1) * kG - 1) / kN;
            rank[u] = atoms_inc(sb + SM_SCNT + db[u] * 4);
        }
#pragma unroll
        for (int u = 0; u < 4; ++u) {
            const uint32_t nl = dd[u] - node_start(db[u]);
            if (rank[u] < kSlot)
                sts32(sb + SM_SLOT + db[u] * 128 + rank[u] * 4, (uint32_t)ss[u] | ((uint32_t)(tid * 4 + u) << 14) | (nl << 25));
        }
    }
    if (warp < 10) named_sync<5, 320>();
    if (warp == 8) {
#pragma unroll 1
        for (int d = lane; d < kG; d += 32)
            if (lds32(sb + SM_SCNT + d * 4) > kSlot) sts32(sb + SM_SLOT + d * 128, kOverflow);
        __syncwarp();
        if (lane == 0) {
            fence_async_smem();
            bulk_store(p.slots + (size_t)b * kG * kSlot, sb + SM_SLOT, kG * 128);
            bulk_commit();
            asm volatile("cp.async.bulk.wait_group 0;" ::: "memory");
            grid_arrive(p.bar);
        }
    } else if (warp == 10) {
#pragma unroll 1
        for (int i = lane; i < kNGrp * kGCap / 2; i += 32) sts128(sb + SM_LIST + i * 16, kPadX, kPadY, kPadX, kPadY);
        named_arrive(12, 64);
    } else if (warp == 9) {
        named_wait(12, 64);
        if (lane == 0) {
            asm volatile("prefetch.tensormap [%0];" ::"l"(&p.ms) : "memory");
            grid_wait(p.bar, target);
            mbar_expect(sb + SM_MBAR + 32, kG * 128);
            tma_load(sb + SM_SLOT, &p.ms, b * kSlot, 0, sb + SM_MBAR + 32);
        }
    } else if (warp == 11) {
        mbar_wait(sb + SM_MBAR, 0);
        if (lane < 6) {
            const int h = lane & 1, m = lane >> 1;
            tma_load(sb + (m == 1 ? SM_WC + h * 2048 : SM_W4 + (m >> 1) * 32768 + h * 16384), m == 0 ? &p.mg : (m == 1 ? &p.mc : &p.mu),
                     h * 64, m == 1 ? 256 : 0, sb + SM_MBAR + (m == 2 ? 24 : 16));
        }
    }
    __syncwarp();
    const int q = lane >> 3, pp = lane & 7;
    if (warp < 8) {
        const int wg = warp >> 2, w4 = warp & 3;
        const uint32_t xlo = ((sb + SM_X) >> 4) | 0x10000u;
        const uint32_t sw = wg * 128 + (((2 * w4 + (q & 1)) ^ ((pp + n0) & 7)) << 4);
#pragma unroll 1
        for (int pair = 0; pair < 4; ++pair) {
            const uint32_t wpair = sb + (pair < 2 ? SM_W0 : SM_W4 - 65536) + pair * 32768;
            mbar_wait(sb + SM_MBAR + pair * 8, 0);
            float acc[40];
            const uint32_t alo = ((wpair + wg * 16384) >> 4) | 0x10000u;
            asm volatile("wgmma.fence.sync.aligned;" ::: "memory");
#pragma unroll
            for (int s = 0; s < 8; ++s)
                wgmma_m64n80k16(acc, make_desc(alo + s * 128), make_desc(xlo + (s >> 2) * 640 + (s & 3) * 2), s);
            asm volatile("wgmma.commit_group.sync.aligned;" ::: "memory");
            asm volatile("wgmma.wait_group.sync.aligned 0;" ::: "memory");
#pragma unroll
            for (int i = 0; i < 40; ++i) asm volatile("" : "+f"(acc[i])::"memory");
            named_sync<1, 256>();
            const uint32_t a0 = wpair + ((q >> 1) * 8 + pp) * 256 + sw;
#pragma unroll
            for (int i = 0; i < 10; i += 2)
                stsm4t(a0 + i * 2048, pack_bf16(acc[4 * i], acc[4 * i + 1]), pack_bf16(acc[4 * i + 2], acc[4 * i + 3]),
                       pack_bf16(acc[4 * i + 4], acc[4 * i + 5]), pack_bf16(acc[4 * i + 6], acc[4 * i + 7]));
            if (pair < 2) named_arrive(9 + pair, 288);
        }
    } else {
        if (warp == 8) {
#pragma unroll 1
            for (int pair = 0; pair < 2; ++pair) {
                named_wait(9 + pair, 288);
                if (lane == 0) {
                    fence_async_smem();
                    bulk_store(p.tab + (size_t)pair * kTab + (size_t)n0 * 256, sb + SM_W0 + pair * 32768 + (n0 - nb) * 256, (n1 - n0) * 256);
                    bulk_commit();
                }
            }
            if (lane == 0) {
                asm volatile("cp.async.bulk.wait_group 0;" ::: "memory");
                grid_arrive(p.bar + 32);
            }
            __syncwarp();
        } else if (warp == 10) {
            mbar_wait(sb + SM_MBAR + 8, 0);
#pragma unroll 1
            for (int i = lane; i < nq; i += 32) asm volatile("prefetch.global.L2 [%0];" ::"l"(p.ea + (size_t)e0 * 32 + i * 128) : "memory");
        }
    }
    {
        const uint32_t c0 = 2 * warp + (lane >> 4);
        auto place = [&](uint32_t rec, uint32_t rank, uint32_t c) {
            if (rank < (uint32_t)kGCap && (rec >> 28) < (uint32_t)kNGrp)
                sts64(sb + SM_LIST + ((rec >> 28) * kGCap + rank) * 8, ((rec & 0x3FFFu) << 8) | ((rec & 7u) << 4),
                      c * (kEPB * 32) + ((rec >> 9) & 0xFFE0u) + ((rec >> 1) & 0x7F000000u));
        };
        auto count = [&](uint32_t rec) {
            return atoms_inc(sb + SM_NCNT + ((rec & 0x3FFFu) < (uint32_t)kN ? (rec >> 28) : 16 + lane) * 4);
        };
        uint32_t rec[6], rank[6], full = 0;
        mbar_wait(sb + SM_MBAR + 32, 0);
#pragma unroll
        for (int i = 0; i < 6; ++i) rec[i] = c0 + 24 * i < kG ? lds32(sb + SM_SLOT + (c0 + 24 * i) * 128 + (lane & 15) * 4) : kSentinel;
#pragma unroll
        for (int i = 0; i < 6; ++i) {
            rank[i] = count(rec[i]);
            full |= ((rec[i] & 0x3FFFu) < (uint32_t)kN ? 1u : 0u) << i;
        }
#pragma unroll
        for (int i = 0; i < 6; ++i) place(rec[i], rank[i], c0 + 24 * i);
#pragma unroll 1
        for (uint32_t m = __reduce_or_sync(0xffffffffu, (lane & 15) == 15 ? full : 0u); m; m &= m - 1) {
            const uint32_t c = c0 + 24 * (__ffs(m) - 1);
            const uint32_t r = lds32(sb + SM_SLOT + c * 128 + 64 + (lane & 15) * 4);
            place(r, count(r), c);
        }
    }
    if (tid == 256) grid_wait(p.bar + 32, target);
    __syncwarp();
    __syncthreads();

    const int g = lane >> 2, t = lane & 3;
    const int lo = n0 - nb, hi = n1 - nb;
    uint32_t cnt = lane < 16 ? lds32(sb + SM_NCNT + lane * 4) : 0;
    const bool slow = __any_sync(0xffffffffu, lane < kNGrp ? cnt > (uint32_t)kGCap : cnt != 0);
    const int ns = (lane < kNGrp && lane * 8 < hi) ? max(1, (int)(cnt + 7) >> 3) : 0;
    int sinc = ns;
#pragma unroll
    for (int o = 1; o < 16; o <<= 1) {
        const int v = __shfl_up_sync(0xffffffffu, sinc, o);
        if (lane >= o) sinc += v;
    }
    const int S = __shfl_sync(0xffffffffu, sinc, 15);
    const int k0 = (S * warp) / kWarps, k1 = (S * (warp + 1)) / kWarps;
    int sgrp = 0;
#pragma unroll
    for (int i = 0; i < kNGrp; ++i) sgrp += __shfl_sync(0xffffffffu, sinc, i) <= k0 + lane;
    sgrp = min(sgrp, kNGrp - 1);
    const int gtab = sinc | (ns << 16);
    uint32_t stab;
    {
        const int gt = __shfl_sync(0xffffffffu, gtab, sgrp);
        const int first = sgrp * kGCap + (k0 + lane - ((gt & 0xFFFF) - (gt >> 16))) * 8;
        stab = (first & 0xFFF) | (sgrp << 24);
    }
    int nsteps = k1 - k0;

    const uint32_t ident = (g == 2 * t) ? 0x00003F00u : ((g == 2 * t + 1) ? 0x3F000000u : 0u);
    const uint32_t xa = (pp ^ q) << 4;
    const uint32_t lrd = pp * 128 + ((q ^ pp) << 4);
    const uint32_t ring = sb + SM_RING + warp * (2 * kRingSlot);
    const uint32_t lbase = sb + SM_LIST;
    const unsigned char* ea_base = p.ea + t * 8;
    uint32_t wc[8][4], at[8][2];
    float agg[8][4];
    int scan_pos = 0;
    if (slow) {
        nsteps = (warp < kNGrp && warp * 8 < hi) ? 1 : 0;
        stab = warp << 24;
    }
    int k = -1;
    uint32_t st_c = 0;
#pragma unroll 1
    for (int ks = -1; ks < nsteps;) {
        int gc = 0, ke = 0, gend = 0;
        bool own = false;
        unsigned imp = 0;
        if (ks >= 0) {
            gc = __shfl_sync(0xffffffffu, stab, ks) >> 24;
            ke = ks + __popc(__ballot_sync(0xffffffffu, (int)(stab >> 24) == gc && lane >= ks && lane < nsteps));
            const int gt = __shfl_sync(0xffffffffu, gtab, gc);
            gend = gt & 0xFFFF;
            own = slow || gend - (gt >> 16) >= k0;
            if (own && !slow)
                imp = __ballot_sync(0xffffffffu, lane > warp && lane < kWarps && (S * lane) / kWarps < gend &&
                                                     (S * (lane + 1)) / kWarps != (S * lane) / kWarps);
            if (ks == 0) {
                mbar_wait(sb + SM_MBAR + 16, 0);
#pragma unroll
                for (int T = 0; T < 8; ++T)
                    ldsm4t(wc[T], sb + SM_WC + (T >> 2) * 2048 + ((q >> 1) * 8 + pp) * 128 + ((((q & 1) ^ pp) << 4) ^ ((2 * T & 7) << 4)));
            }
            const uint32_t oi = own ? ident : 0u;
            const uint32_t ra = sb + SM_W4 + (gc * 8 + pp) * 256;
#pragma unroll
            for (int u = 0; u < 4; ++u) {
                const uint32_t o = (u >> 1) * 128 + (((4 * (u & 1) + q) ^ ((pp + n0) & 7)) << 4);
                uint32_t r[4];
                ldsm4t(r, ra + o);
                at[2 * u][0] = r[0]; at[2 * u][1] = r[1]; at[2 * u + 1][0] = r[2]; at[2 * u + 1][1] = r[3];
                ldsm4t(r, ra + 32768 + o);
                mma16z(agg[2 * u], r[0], r[1], r[0], r[1], oi, oi);
                mma16z(agg[2 * u + 1], r[2], r[3], r[2], r[3], oi, oi);
            }
        }
        const uint32_t nlb = gc * 8 + 2 * t;
        do {
            if (slow && ks >= 0) {
                int n = 0;
                cp_wait<0>();
#pragma unroll 1
                while (scan_pos < kE && n <= kGCap - 32) {
                    const int e = scan_pos + lane;
                    const int d = e < kE ? __ldg(p.dst + e) - nb : -1;
                    const bool m = d >= lo && d < hi && (d >> 3) == warp;
                    const unsigned bal = __ballot_sync(0xffffffffu, m);
                    if (m) {
                        const uint32_t s = __ldg(p.src + e);
                        sts64(lbase + (warp * kGCap + n + __popc(bal & ((1u << lane) - 1))) * 8, (s << 8) | ((s & 7u) << 4), (uint32_t)e * 32 + ((uint32_t)d << 24));
                    }
                    n += __popc(bal);
                    scan_pos += 32;
                }
                if (lane < 8) sts64(lbase + (warp * kGCap + n + lane) * 8, kPadX, kPadY);
                __syncwarp();
                nsteps = ke = max(1, (n + 7) >> 3);
                stab = ((warp * kGCap + lane * 8) & 0xFFF) | (warp << 24);
                k = -1;
            }
#pragma unroll 1
            for (; k < ke; ++k) {
                uint32_t st_n = 0;
                if (k + 1 < nsteps) {
                    st_n = __shfl_sync(0xffffffffu, stab, k + 1);
                    const uint32_t la = lbase + (st_n & 0xFFF) * 8;
                    const uint32_t slot = ring + ((k + 1) & 1) * kRingSlot;
                    const uint32_t wa = lds32(la + q * 8), wb = lds32(la + q * 8 + 32), wy = lds32(la + g * 8 + 4);
                    const unsigned char* pa = p.tab + ((wa & 0xFFFFFFF0u) ^ xa);
                    const unsigned char* pb = p.tab + ((wb & 0xFFFFFFF0u) ^ xa ^ 64u);
                    const uint32_t d = slot + lane * 16, na = (wa & 1) ? 0 : 16, nb2 = (wb & 1) ? 0 : 16;
                    cp16z(d, pa, na);
                    cp16z(d + 2048, pa + kTab, na);
                    cp16z(d + 512, pb, nb2);
                    cp16z(d + 2560, pb + kTab, nb2);
                    cp16z(d + 1024, pa + 128, na);
                    cp16z(d + 3072, pa + kTab + 128, na);
                    cp16z(d + 1536, pb + 128, nb2);
                    cp16z(d + 3584, pb + kTab + 128, nb2);
                    cp8z(slot + 4096 + lane * 8, ea_base + (wy & 0xFFFFFFu), wy != kPadY ? 8 : 0);
                }
                cp_commit();
                if (k >= 0) {
                    const uint32_t slot = ring + (k & 1) * kRingSlot;
                    const uint32_t wy = lds32(lbase + ((st_c & 0xFFF) + g) * 8 + 4);
                    cp_wait<1>();
                    __syncwarp();
                    uint32_t ea0, ea1;
                    asm volatile("ldmatrix.sync.aligned.m8n8.x2.shared.b16 {%0,%1}, [%2];" : "=r"(ea0), "=r"(ea1) : "r"(slot + 4096 + pp * 32 + (q & 1) * 16) : "memory");
                    ea0 = hfma2(ea0, 0x3F003F00u, 0x80008000u);
                    ea1 = hfma2(ea1, 0x3F003F00u, 0x80008000u);
                    const uint32_t dd = (wy >> 24) - nlb;
                    const uint32_t sT = dd == 0 ? 0x00003F00u : (dd == 1 ? 0x3F000000u : 0u);
                    const uint32_t sA = movm_t(sT);
#pragma unroll
                    for (int u = 0; u < 4; ++u) {
                        uint32_t bq[4], vq[4];
                        const uint32_t la = slot + ((u & 1) ? (lrd ^ 64u) : lrd) + (u >> 1) * 1024;
                        ldsm4(bq, la);
                        ldsm4t(vq, la + 2048);
#pragma unroll
                        for (int s = 0; s < 2; ++s) {
                            const int T = 2 * u + s;
                            float z[4];
                            mma16z(z, wc[T][0], wc[T][1], wc[T][2], wc[T][3], ea0, ea1);
                            mma8(z, at[T][0], at[T][1], sT);
                            mma16(z, ident, 0u, 0u, ident, bq[2 * s], bq[2 * s + 1]);
                            const uint32_t t01 = pack_bf16(tanh_fast(z[0]), tanh_fast(z[1]));
                            const uint32_t t23 = pack_bf16(tanh_fast(z[2]), tanh_fast(z[3]));
                            mma8(agg[T], hfma2(vq[2 * s], t01, vq[2 * s]), hfma2(vq[2 * s + 1], t23, vq[2 * s + 1]), sA);
                        }
                    }
                    __syncwarp();
                }
                st_c = st_n;
            }
        } while (slow && ks >= 0 && scan_pos < kE);
        if (ks < 0) {
            ks = 0;
            continue;
        }
        if (!own) {
            const uint32_t ex = exp_slot(sb, warp) + lane * 16;
#pragma unroll
            for (int T = 0; T < 8; ++T)
                sts128(ex + T * 512, __float_as_uint(agg[T][0]), __float_as_uint(agg[T][1]), __float_as_uint(agg[T][2]),
                       __float_as_uint(agg[T][3]));
            mbar_arrive(sb + SM_MBAR + 40 + warp * 8);
        } else {
#pragma unroll 1
            for (unsigned m = imp; m; m &= m - 1) {
                const int w2 = __ffs(m) - 1;
                const uint32_t ex = exp_slot(sb, w2) + lane * 16;
                mbar_wait(sb + SM_MBAR + 40 + w2 * 8, 0);
#pragma unroll
                for (int T = 0; T < 8; ++T) {
                    const uint4 v = lds128(ex + T * 512);
                    agg[T][0] += __uint_as_float(v.x);
                    agg[T][1] += __uint_as_float(v.y);
                    agg[T][2] += __uint_as_float(v.z);
                    agg[T][3] += __uint_as_float(v.w);
                }
            }
            const uint32_t st = sb + SM_W4 + gc * 2048;
            __syncwarp();
#pragma unroll
            for (int u = 0; u < 4; ++u) {
                uint32_t pk[4];
#pragma unroll
                for (int j = 0; j < 4; ++j) {
                    const float h0 = 0.5f * agg[2 * u + (j >> 1)][2 * (j & 1)], h1 = 0.5f * agg[2 * u + (j >> 1)][2 * (j & 1) + 1];
                    pk[j] = pack_bf16(fmaf(h0, tanh_fast(h0), h0), fmaf(h1, tanh_fast(h1), h1));
                }
                stsm4t(st + pp * 256 + (u >> 1) * 128 + (((4 * (u & 1) + q) ^ pp) << 4), pk[0], pk[1], pk[2], pk[3]);
            }
            __syncwarp();
            {
                const int c = lane & 15, r0 = lane >> 4;
                unsigned char* o = p.out + (size_t)(nb + gc * 8 + r0) * 256 + c * 16;
                uint4 v[4];
#pragma unroll
                for (int i = 0; i < 4; ++i) v[i] = lds128(st + (r0 + 2 * i) * 256 + (c >> 3) * 128 + (((c & 7) ^ (r0 + 2 * i)) << 4));
#pragma unroll
                for (int i = 0; i < 4; ++i) {
                    const int nl = gc * 8 + r0 + 2 * i;
                    if (nl >= lo && nl < hi) *reinterpret_cast<uint4*>(o + i * 512) = v[i];
                }
            }
        }
        ks = slow ? nsteps : ke;
    }
}

}

typedef CUresult (*EncodeTiledFn)(CUtensorMap*, CUtensorMapDataType, cuuint32_t, void*, const cuuint64_t*, const cuuint64_t*,
                                  const cuuint32_t*, const cuuint32_t*, CUtensorMapInterleave, CUtensorMapSwizzle,
                                  CUtensorMapL2promotion, CUtensorMapFloatOOBfill);

static void encode_map(EncodeTiledFn enc, CUtensorMap* m, const void* base, int rows, int box_rows) {
    const cuuint64_t dims[2] = {128, (cuuint64_t)rows};
    const cuuint64_t strides[1] = {256};
    const cuuint32_t box[2] = {64, (cuuint32_t)box_rows};
    const cuuint32_t estr[2] = {1, 1};
    enc(m, CU_TENSOR_MAP_DATA_TYPE_BFLOAT16, 2, const_cast<void*>(base), dims, strides, box, estr, CU_TENSOR_MAP_INTERLEAVE_NONE,
        CU_TENSOR_MAP_SWIZZLE_128B, CU_TENSOR_MAP_L2_PROMOTION_L2_256B, CU_TENSOR_MAP_FLOAT_OOB_FILL_NONE);
}

extern "C" void kernel_launch(void* const* d_in, const int* in_sizes, int n_in, void* d_out, int out_size) {
    (void)in_sizes; (void)n_in; (void)out_size;
    static EncodeTiledFn enc = nullptr;
    if (!enc) {
        cudaFuncSetAttribute(egc::egc_kernel, cudaFuncAttributeMaxDynamicSharedMemorySize, egc::SM_TOTAL);
        void* fn = nullptr;
        cudaDriverEntryPointQueryResult qr;
        cudaGetDriverEntryPoint("cuTensorMapEncodeTiled", &fn, cudaEnableDefault, &qr);
        enc = (EncodeTiledFn)fn;
    }
    static void *slots_addr = nullptr, *tab_addr = nullptr, *bar_addr = nullptr;
    if (!slots_addr) {
        cudaGetSymbolAddress(&slots_addr, egc::g_slots);
        cudaGetSymbolAddress(&tab_addr, egc::g_T);
        cudaGetSymbolAddress(&bar_addr, egc::g_bar);
    }
    egc::Params p;
    p.tab = (unsigned char*)tab_addr;
    p.slots = (uint32_t*)slots_addr;
    p.bar = (unsigned*)bar_addr;
    {
        const cuuint64_t dims[2] = {egc::kG * egc::kSlot, egc::kG};
        const cuuint64_t strides[1] = {egc::kG * egc::kSlot * 4};
        const cuuint32_t box[2] = {egc::kSlot, egc::kG};
        const cuuint32_t estr[2] = {1, 1};
        enc(&p.ms, CU_TENSOR_MAP_DATA_TYPE_UINT32, 2, slots_addr, dims, strides, box, estr, CU_TENSOR_MAP_INTERLEAVE_NONE,
            CU_TENSOR_MAP_SWIZZLE_NONE, CU_TENSOR_MAP_L2_PROMOTION_NONE, CU_TENSOR_MAP_FLOAT_OOB_FILL_NONE);
    }
    encode_map(enc, &p.mx, d_in[0], egc::kN, egc::kRows);
    encode_map(enc, &p.mg, d_in[6], 272, 128);
    encode_map(enc, &p.mc, d_in[6], 272, 16);
    encode_map(enc, &p.mv, d_in[5], 128, 128);
    encode_map(enc, &p.mu, d_in[4], 128, 128);
    p.ea = (const unsigned char*)d_in[1];
    p.src = (const int*)d_in[2];
    p.dst = (const int*)d_in[3];
    p.out = (unsigned char*)d_out;
    egc::egc_kernel<<<egc::kG, egc::kThreads, egc::SM_TOTAL, cudaStreamPerThread>>>(p);
}
```
